```python
import torch

def _softmax(x, axis=-1):
    return torch.softmax(x, dim=axis)

def _gelu(x):
    return torch.nn.functional.gelu(x, approximate='tanh')

def _silu(x):
    return torch.nn.functional.silu(x)

def _sigmoid(x):
    return torch.sigmoid(x)

def _layernorm(x, axis=-1, eps=1e-05):
    m = x.mean(dim=axis, keepdim=True)
    v = x.var(dim=axis, keepdim=True, unbiased=False)
    return (x - m) / torch.sqrt(v + eps)

def _scatter_add(tgt, idx, src, axis=0):
    return tgt.clone().index_add_(axis, idx, src)

def _segment_sum(src, seg, n):
    out = torch.zeros((n,) + src.shape[1:], dtype=src.dtype)
    return out.index_add_(0, seg, src)

def _pad(x, pw):
    flat = tuple((v for pair in reversed(pw) for v in pair))
    return torch.nn.functional.pad(x, flat)
kernel_name = 'gated_mix__memory_aug_recurrent_mem_tr__moe_arch_mod__prompt'

def setup_inputs():

    _w = lambda a: (lambda t: t.to(torch.bfloat16) if t.is_floating_point() else t)(torch.as_tensor(a))

    def _A_setup():
        B, S, Dm = (1, 2048, 448)
        H, Dh = (16, 256)
        M, seg = (8, 32)
        seg = min(seg, S)
        S = S // seg * seg
        return {'x': _w((lambda *s: torch.randn(*s, dtype=torch.bfloat16) * 0.05)(B, S, Dm)), 'mem0': _w((lambda *s: torch.randn(*s, dtype=torch.bfloat16) * 0.8)(B, M, Dm)), 'Wq': _w((lambda *s: torch.randn(*s, dtype=torch.bfloat16) * 1.6)(Dm, H, Dh) * Dm ** (-0.5)), 'Wk': _w((lambda *s: torch.randn(*s, dtype=torch.bfloat16) * 1.6)(Dm, H, Dh) * Dm ** (-0.5)), 'Wv': _w((lambda *s: torch.randn(*s, dtype=torch.bfloat16) * 0.8)(Dm, H, Dh) * Dm ** (-0.5)), 'Wo': _w((lambda *s: torch.randn(*s, dtype=torch.bfloat16) * 0.8)(H, Dh, Dm) * (H * Dh) ** (-0.5)), 'seg_len': seg}
    _A_in = _A_setup()

    def _B_setup():
        B, S, D, F, C = (1, 2048, 448, 1792, 1)
        return {'x': _w((lambda *s: torch.randn(*s, dtype=torch.bfloat16) * 0.05)(B, S, D)), 'w_r': _w((lambda *s: torch.randn(*s, dtype=torch.bfloat16) * 1.6)(D)), 'w_gate': _w((lambda *s: torch.randn(*s, dtype=torch.bfloat16) * 0.2)(D, F)), 'w_up': _w((lambda *s: torch.randn(*s, dtype=torch.bfloat16) * 0.2)(D, F)), 'w_down': _w((lambda *s: torch.randn(*s, dtype=torch.bfloat16) * 0.2)(F, D))}
    _B_in = _B_setup()
    return {'A_x': _A_in['x'], 'A_mem0': _A_in['mem0'], 'A_Wq': _A_in['Wq'], 'A_Wk': _A_in['Wk'], 'A_Wv': _A_in['Wv'], 'A_Wo': _A_in['Wo'], 'A_seg_len': _A_in['seg_len'], 'B_x': _B_in['x'], 'B_w_r': _B_in['w_r'], 'B_w_gate': _B_in['w_gate'], 'B_w_up': _B_in['w_up'], 'B_w_down': _B_in['w_down'], 'gate_w': _w((lambda *s: torch.randn(*s, dtype=torch.bfloat16) * 0.05)(448) * 16.0)}

def reference(A_x, A_mem0, A_Wq, A_Wk, A_Wv, A_Wo, A_seg_len, B_x, B_w_r, B_w_gate, B_w_up, B_w_down, gate_w):

    def _A_ref(x, mem0, Wq, Wk, Wv, Wo, seg_len):
        B, S, Dm = x.shape
        H, Dh = (Wq.shape[1], Wq.shape[2])
        M = mem0.shape[1]
        scale = Dh ** (-0.5)
        n_seg = S // seg_len
        L = M + seg_len
        idx = torch.arange(L)
        mask = (idx[:, None] < M) | (idx[:, None] >= idx[None, :])
        mem = mem0
        outs = []
        for s in range(n_seg):
            xs = x[:, s * seg_len:(s + 1) * seg_len, :].clone()
            h = torch.concatenate([mem, xs], axis=1)
            q = torch.einsum('btd,dhe->bhte', h, Wq)
            k = torch.einsum('btd,dhe->bhte', h, Wk)
            v = torch.einsum('btd,dhe->bhte', h, Wv)
            scores = torch.einsum('bhqe,bhke->bhqk', q, k) * scale
            scores = torch.where(mask[None, None], scores, -1000000000.0)
            p = _softmax(scores, axis=-1)
            o = torch.einsum('bhqk,bhke->bhqe', p, v)
            o = torch.einsum('bhte,hed->btd', o, Wo)
            mem = o[:, :M, :].clone()
            outs.append(o[:, M:, :])
        return torch.concatenate(outs, axis=1)

    def _B_ref(x, w_r, w_gate, w_up, w_down):
        B, S, D = x.shape
        C = 1
        r = x @ w_r
        idx = torch.argsort(-r, axis=-1)[:, :C]
        idx_e = (lambda x, n, axis: torch.repeat_interleave(x, n, dim=axis))(idx.reshape(B, C, 1), D, axis=2)
        x_sel = (lambda x, i, axis: torch.take_along_dim(x, i, dim=axis))(x, idx_e, axis=1)
        g = _silu(x_sel @ w_gate)
        u = x_sel @ w_up
        y = g * u @ w_down
        r_sel = _sigmoid((lambda x, i, axis: torch.take_along_dim(x, i, dim=axis))(r, idx, axis=1))
        y = y * r_sel.reshape(B, C, 1)
        b_off = (torch.arange(B) * S).reshape(B, 1)
        flat_idx = (idx + b_off).reshape(B * C)
        zero = (x * 0.0).reshape(B * S, D)
        upd = _scatter_add(zero, flat_idx, y.reshape(B * C, D), axis=0)
        return x + upd.reshape(B, S, D)
    x = A_x
    g = _sigmoid((x * gate_w).sum(-1, keepdims=True))
    a = _A_ref(x, A_mem0, A_Wq, A_Wk, A_Wv, A_Wo, A_seg_len)
    b = _B_ref(x, B_w_r, B_w_gate, B_w_up, B_w_down)
    return g * a + (1 - g) * b
```

```cpp
#include <cuda_runtime.h>
#include <cuda.h>
#include <cuda_bf16.h>
#include <stdint.h>

typedef __nv_bfloat16 bf16;

constexpr int SEQ = 2048, DM = 448, NH = 16, DH = 256, NSEG = 64, FF = 1792;
constexpr int NTHREADS = 384;
constexpr int SMEM_BYTES = 232448;

__device__ uint4  g_WC [32 * 2 * 7 * 28 * 8 * 8];
__device__ uint4  g_KAF[64 * 16 * 4 * 2 * 7 * 32];
__device__ uint4  g_VBF[64 * 16 * 28 * 2 * 32];
__device__ float4 g_SXX[64 * 16 * 2 * 2 * 4 * 32];
__device__ float4 g_SXM[64 * 16 * 4 * 2 * 32];
__device__ uint4  g_UF [64 * 8 * 28 * 32];
__device__ float  g_gate[SEQ];
__device__ float  g_r[SEQ];
__device__ float  g_ypart[28 * DM];
__device__ int    g_sel;
__device__ uint4 g_mbox_raw[4 * 4 * 4 * 512 + 512];
#define g_mbox (reinterpret_cast<uint4*>((reinterpret_cast<uintptr_t>(g_mbox_raw) + 8191) & ~(uintptr_t)8191))
struct Flags {
  unsigned fw[32];
  unsigned fkv[64 * 8];
  unsigned fseg[64];
  unsigned fffn;
  unsigned frec;
  unsigned fx;
  unsigned q_w, q_gemm, q_tail;
  unsigned pad[10];
};
constexpr int FLAG_WORDS = sizeof(Flags) / 4;
__device__ Flags g_flags[2];
__device__ unsigned g_epoch[256];
__device__ unsigned g_err;
#define PROF_CTA(cta, i)
#define PROF_VAL(s, i, v)
#define PROF_CLK(cta, i)
#define PROF_REC(s, i)

__device__ __forceinline__ uint32_t smem_u32(const void* p) { return (uint32_t)__cvta_generic_to_shared(p); }
__device__ __forceinline__ uint32_t mapa(uint32_t a, uint32_t r) { uint32_t d; asm volatile("mapa.shared::cluster.u32 %0, %1, %2;" : "=r"(d) : "r"(a), "r"(r)); return d; }
__device__ __forceinline__ void mbar_init(uint32_t b, int n) { asm volatile("mbarrier.init.shared::cta.b64 [%0], %1;" ::"r"(b), "r"(n) : "memory"); }
__device__ __forceinline__ void mbar_expect(uint32_t b, int tx) { asm volatile("mbarrier.arrive.expect_tx.shared::cta.b64 _, [%0], %1;" ::"r"(b), "r"(tx) : "memory"); }
__device__ __forceinline__ void mbar_arrive(uint32_t b) { asm volatile("mbarrier.arrive.shared::cta.b64 _, [%0];" ::"r"(b) : "memory"); }
__device__ __forceinline__ void mbar_arrive_cluster(uint32_t b) { asm volatile("mbarrier.arrive.release.cluster.shared::cluster.b64 _, [%0];" ::"r"(b) : "memory"); }
__device__ __forceinline__ bool mbar_try(uint32_t b, uint32_t par) {
  uint32_t ok;
  asm volatile("{.reg .pred p; mbarrier.try_wait.parity.shared::cta.b64 p, [%1], %2; selp.u32 %0,1,0,p;}" : "=r"(ok) : "r"(b), "r"(par) : "memory");
  return ok;
}
struct Spin {
  int it = 0;
  __device__ __forceinline__ bool give_up(unsigned code) {
    if ((++it & 31) != 0) return false;
    if (it > (1 << 15)) g_err = code;
    return *reinterpret_cast<volatile unsigned*>(&g_err) != 0;
  }
};
__device__ __forceinline__ void mbar_wait(uint32_t b, uint32_t par) {
  asm volatile("{\n.reg .pred p, q;\n.reg .u32 c;\nmov.u32 c, 0;\n"
               "WL: add.u32 c, c, 1;\n"
               "mbarrier.try_wait.parity.shared::cta.b64 p, [%0], %1;\n"
               "setp.lt.and.u32 q, c, 16384, !p;\n"
               "@q bra WL;\n}" ::"r"(b), "r"(par) : "memory");
}
__device__ __forceinline__ uint32_t now() { uint32_t c; asm volatile("mov.u32 %0, %%clock;" : "=r"(c)); return c; }
__device__ __forceinline__ void delay_from(uint32_t c0, uint32_t n) { while (now() - c0 < n) {} }
__device__ __forceinline__ void delay(uint32_t n) {
  uint32_t c0, c1;
  asm volatile("mov.u32 %0, %%clock;" : "=r"(c0));
  do { asm volatile("mov.u32 %0, %%clock;" : "=r"(c1)); } while (c1 - c0 < n);
}
__device__ __forceinline__ void bar_sync(int id, int n) { asm volatile("bar.sync %0, %1;" ::"r"(id), "r"(n) : "memory"); }
__device__ __forceinline__ void bar_arrive(int id, int n) { asm volatile("bar.arrive %0, %1;" ::"r"(id), "r"(n) : "memory"); }
__device__ __forceinline__ void cluster_sync() { asm volatile("barrier.cluster.arrive.aligned; barrier.cluster.wait.aligned;" ::: "memory"); }
__device__ __forceinline__ void fence_async_smem() { asm volatile("fence.proxy.async.shared::cta;" ::: "memory"); }
__device__ __forceinline__ void fence_async_all() { asm volatile("fence.proxy.async;" ::: "memory"); }
__device__ __forceinline__ void fence_gpu() { asm volatile("fence.acq_rel.gpu;" ::: "memory"); }
__device__ __forceinline__ void red_add(unsigned* p, unsigned v) { asm volatile("red.relaxed.gpu.global.add.u32 [%0], %1;" ::"l"(p), "r"(v) : "memory"); }
__device__ __forceinline__ unsigned ld_acq(const unsigned* p) { unsigned v; asm volatile("ld.acquire.gpu.global.u32 %0, [%1];" : "=r"(v) : "l"(p) : "memory"); return v; }
__device__ __forceinline__ void flag_wait(const unsigned* p, unsigned target) {
  Spin sp;
  while (ld_acq(p) < target) { if (sp.give_up(2)) break; }
}
__device__ __forceinline__ void bulk_g2s(uint32_t dst, const void* src, uint32_t n, uint32_t mb) {
  asm volatile("cp.async.bulk.shared::cluster.global.mbarrier::complete_tx::bytes [%0], [%1], %2, [%3];" ::"r"(dst), "l"(src), "r"(n), "r"(mb) : "memory");
}
__device__ __forceinline__ void bulk_g2s_mc(uint32_t dst, const void* src, uint32_t n, uint32_t mb, uint16_t mask) {
  asm volatile("cp.async.bulk.shared::cluster.global.mbarrier::complete_tx::bytes.multicast::cluster [%0], [%1], %2, [%3], %4;" ::"r"(dst), "l"(src), "r"(n), "r"(mb), "h"(mask) : "memory");
}
__device__ __forceinline__ void tma2d(uint32_t dst, const CUtensorMap* tm, int c0, int c1, uint32_t mb) {
  asm volatile("cp.async.bulk.tensor.2d.shared::cluster.global.mbarrier::complete_tx::bytes [%0], [%1, {%3, %4}], [%2];" ::"r"(dst), "l"(tm), "r"(mb), "r"(c0), "r"(c1) : "memory");
}
__device__ __forceinline__ void tma3d(uint32_t dst, const CUtensorMap* tm, int c0, int c1, int c2, uint32_t mb) {
  asm volatile("cp.async.bulk.tensor.3d.shared::cluster.global.mbarrier::complete_tx::bytes [%0], [%1, {%3, %4, %5}], [%2];" ::"r"(dst), "l"(tm), "r"(mb), "r"(c0), "r"(c1), "r"(c2) : "memory");
}
__device__ __forceinline__ void tma2d_prefetch(const CUtensorMap* tm, int c0, int c1) {
  asm volatile("cp.async.bulk.prefetch.tensor.2d.L2.global [%0, {%1, %2}];" ::"l"(tm), "r"(c0), "r"(c1) : "memory");
}
__device__ __forceinline__ void warp_publish(unsigned* flag, int lane) {
  asm volatile("fence.proxy.async;" ::: "memory");
  __syncwarp();
  if (lane == 0) { fence_gpu(); red_add(flag, 1); }
}
__device__ __forceinline__ void cp16(uint32_t dst, const void* src) { asm volatile("cp.async.cg.shared.global [%0], [%1], 16;" ::"r"(dst), "l"(src) : "memory"); }
__device__ __forceinline__ void cp_commit() { asm volatile("cp.async.commit_group;" ::: "memory"); }
template <int N> __device__ __forceinline__ void cp_wait() { asm volatile("cp.async.wait_group %0;" ::"n"(N) : "memory"); }
__device__ __forceinline__ void st_async_v4(uint32_t a, uint32_t x, uint32_t y, uint32_t z, uint32_t w, uint32_t mb) {
  asm volatile("st.async.weak.shared::cluster.mbarrier::complete_tx::bytes.v4.b32 [%0], {%1,%2,%3,%4}, [%5];" ::"r"(a), "r"(x), "r"(y), "r"(z), "r"(w), "r"(mb) : "memory");
}
__device__ __forceinline__ void st_async_v2f(uint32_t a, float x, float y, uint32_t mb) {
  asm volatile("st.async.weak.shared::cluster.mbarrier::complete_tx::bytes.v2.f32 [%0], {%1,%2}, [%3];" ::"r"(a), "f"(x), "f"(y), "r"(mb) : "memory");
}
__device__ __forceinline__ void st_async_b32(uint32_t a, uint32_t x, uint32_t mb) {
  asm volatile("st.async.weak.shared::cluster.mbarrier::complete_tx::bytes.b32 [%0], %1, [%2];" ::"r"(a), "r"(x), "r"(mb) : "memory");
}
__device__ __forceinline__ uint4 ld_poll(const void* p) {
  uint4 v;
  asm volatile("{.reg .b128 t; ld.relaxed.gpu.global.b128 t, [%4]; mov.b128 {%0,%1,%2,%3}, t;}" : "=r"(v.x), "=r"(v.y), "=r"(v.z), "=r"(v.w) : "l"(p) : "memory");
  return v;
}
__device__ __forceinline__ void st_relaxed(void* p, uint32_t v) { asm volatile("st.relaxed.gpu.global.u32 [%0], %1;" ::"l"(p), "r"(v) : "memory"); }
__device__ __forceinline__ uint32_t pack2(float lo, float hi) { uint32_t d; asm("cvt.rn.bf16x2.f32 %0, %1, %2;" : "=r"(d) : "f"(hi), "f"(lo)); return d; }
__device__ __forceinline__ float bf_lo(uint32_t w) { return __uint_as_float(w << 16); }
__device__ __forceinline__ float bf_hi(uint32_t w) { return __uint_as_float(w & 0xffff0000u); }
__device__ __forceinline__ float rbf(float x) { return __bfloat162float(__float2bfloat16_rn(x)); }
__device__ __forceinline__ float ex2(float x) { float y; asm("ex2.approx.ftz.f32 %0, %1;" : "=f"(y) : "f"(x)); return y; }
__device__ __forceinline__ float rcp(float x) { float y; asm("rcp.approx.ftz.f32 %0, %1;" : "=f"(y) : "f"(x)); return y; }
__device__ __forceinline__ uint32_t movm(uint32_t a) { uint32_t d; asm volatile("movmatrix.sync.aligned.m8n8.trans.b16 %0, %1;" : "=r"(d) : "r"(a)); return d; }
__device__ __forceinline__ void mma(float (&c)[4], uint32_t a0, uint32_t a1, uint32_t a2, uint32_t a3, uint32_t b0, uint32_t b1) {
  asm volatile("mma.sync.aligned.m16n8k16.row.col.f32.bf16.bf16.f32 {%0,%1,%2,%3}, {%4,%5,%6,%7}, {%8,%9}, {%0,%1,%2,%3};"
               : "+f"(c[0]), "+f"(c[1]), "+f"(c[2]), "+f"(c[3]) : "r"(a0), "r"(a1), "r"(a2), "r"(a3), "r"(b0), "r"(b1));
}
__device__ __forceinline__ void mma0(float (&c)[4], uint32_t a0, uint32_t a1, uint32_t a2, uint32_t a3, uint32_t b0, uint32_t b1) {
  asm volatile("mma.sync.aligned.m16n8k16.row.col.f32.bf16.bf16.f32 {%0,%1,%2,%3}, {%4,%5,%6,%7}, {%8,%9}, {%10,%10,%10,%10};"
               : "=f"(c[0]), "=f"(c[1]), "=f"(c[2]), "=f"(c[3]) : "r"(a0), "r"(a1), "r"(a2), "r"(a3), "r"(b0), "r"(b1), "f"(0.f));
}
__device__ __forceinline__ void mma8(float (&c)[4], uint32_t a0, uint32_t a1, uint32_t b0) {
  asm volatile("mma.sync.aligned.m16n8k8.row.col.f32.bf16.bf16.f32 {%0,%1,%2,%3}, {%4,%5}, {%6}, {%0,%1,%2,%3};"
               : "+f"(c[0]), "+f"(c[1]), "+f"(c[2]), "+f"(c[3]) : "r"(a0), "r"(a1), "r"(b0));
}
__device__ __forceinline__ void mma8z(float (&c)[4], uint32_t a0, uint32_t a1, uint32_t b0) {
  asm volatile("mma.sync.aligned.m16n8k8.row.col.f32.bf16.bf16.f32 {%0,%1,%2,%3}, {%4,%5}, {%6}, {%7,%7,%7,%7};"
               : "=f"(c[0]), "=f"(c[1]), "=f"(c[2]), "=f"(c[3]) : "r"(a0), "r"(a1), "r"(b0), "f"(0.f));
}
__device__ __forceinline__ bool mbar_test(uint32_t b, uint32_t par) {
  uint32_t ok;
  asm volatile("{.reg .pred p; mbarrier.test_wait.parity.shared::cta.b64 p, [%1], %2; selp.u32 %0,1,0,p;}" : "=r"(ok) : "r"(b), "r"(par) : "memory");
  return ok;
}
__device__ __forceinline__ void ldsm4(uint32_t& r0, uint32_t& r1, uint32_t& r2, uint32_t& r3, uint32_t a) {
  asm volatile("ldmatrix.sync.aligned.m8n8.x4.shared.b16 {%0,%1,%2,%3}, [%4];" : "=r"(r0), "=r"(r1), "=r"(r2), "=r"(r3) : "r"(a) : "memory");
}
__device__ __forceinline__ void ldsm4t(uint32_t& r0, uint32_t& r1, uint32_t& r2, uint32_t& r3, uint32_t a) {
  asm volatile("ldmatrix.sync.aligned.m8n8.x4.trans.shared.b16 {%0,%1,%2,%3}, [%4];" : "=r"(r0), "=r"(r1), "=r"(r2), "=r"(r3) : "r"(a) : "memory");
}
__device__ __forceinline__ void ldsm2t(uint32_t& r0, uint32_t& r1, uint32_t a) {
  asm volatile("ldmatrix.sync.aligned.m8n8.x2.trans.shared.b16 {%0,%1}, [%2];" : "=r"(r0), "=r"(r1) : "r"(a) : "memory");
}
__device__ __forceinline__ uint4 lds128(uint32_t a) { uint4 v; asm volatile("ld.shared.v4.u32 {%0,%1,%2,%3}, [%4];" : "=r"(v.x), "=r"(v.y), "=r"(v.z), "=r"(v.w) : "r"(a) : "memory"); return v; }
__device__ __forceinline__ float4 lds128f(uint32_t a) { float4 v; asm volatile("ld.shared.v4.f32 {%0,%1,%2,%3}, [%4];" : "=f"(v.x), "=f"(v.y), "=f"(v.z), "=f"(v.w) : "r"(a) : "memory"); return v; }
__device__ __forceinline__ uint2 lds64(uint32_t a) { uint2 v; asm volatile("ld.shared.v2.u32 {%0,%1}, [%2];" : "=r"(v.x), "=r"(v.y) : "r"(a) : "memory"); return v; }
__device__ __forceinline__ float2 lds64f(uint32_t a) { float2 v; asm volatile("ld.shared.v2.f32 {%0,%1}, [%2];" : "=f"(v.x), "=f"(v.y) : "r"(a) : "memory"); return v; }
__device__ __forceinline__ void sts128(uint32_t a, uint32_t x, uint32_t y, uint32_t z, uint32_t w) { asm volatile("st.shared.v4.u32 [%0], {%1,%2,%3,%4};" ::"r"(a), "r"(x), "r"(y), "r"(z), "r"(w) : "memory"); }
__device__ __forceinline__ void sts128f(uint32_t a, float x, float y, float z, float w) { asm volatile("st.shared.v4.f32 [%0], {%1,%2,%3,%4};" ::"r"(a), "f"(x), "f"(y), "f"(z), "f"(w) : "memory"); }
__device__ __forceinline__ void sts64(uint32_t a, uint32_t x, uint32_t y) { asm volatile("st.shared.v2.u32 [%0], {%1,%2};" ::"r"(a), "r"(x), "r"(y) : "memory"); }
__device__ __forceinline__ void sts64f(uint32_t a, float x, float y) { asm volatile("st.shared.v2.f32 [%0], {%1,%2};" ::"r"(a), "f"(x), "f"(y) : "memory"); }
__device__ __forceinline__ void sts32(uint32_t a, uint32_t x) { asm volatile("st.shared.u32 [%0], %1;" ::"r"(a), "r"(x) : "memory"); }
__device__ __forceinline__ void wg_fence() { asm volatile("wgmma.fence.sync.aligned;" ::: "memory"); }
__device__ __forceinline__ void wg_commit() { asm volatile("wgmma.commit_group.sync.aligned;" ::: "memory"); }
template <int N> __device__ __forceinline__ void wg_wait() { asm volatile("wgmma.wait_group.sync.aligned %0;" ::"n"(N) : "memory"); }
__device__ __forceinline__ uint64_t mkdesc(uint32_t addr, uint32_t lbo, uint32_t sbo) {
  return (uint64_t)((addr >> 4) & 0x3fff) | ((uint64_t)(lbo >> 4) << 16) | ((uint64_t)(sbo >> 4) << 32);
}
__device__ __forceinline__ uint64_t mkdesc_sw(uint32_t addr) {
  return (uint64_t)((addr >> 4) & 0x3fff) | ((uint64_t)1 << 16) | ((uint64_t)64 << 32) | ((uint64_t)1 << 62);
}
__device__ __forceinline__ uint32_t opaque(uint32_t x) { asm volatile("" : "+r"(x)); return x; }
__device__ __forceinline__ int read_tid() { int t; asm volatile("mov.u32 %0, %%tid.x;" : "=r"(t)); return t; }
template <int N> __device__ __forceinline__ void reg_inc() { asm volatile("setmaxnreg.inc.sync.aligned.u32 %0;" ::"n"(N)); }
template <int N> __device__ __forceinline__ void reg_dec() { asm volatile("setmaxnreg.dec.sync.aligned.u32 %0;" ::"n"(N)); }
__device__ __forceinline__ void wgmma224(float (&d)[112], uint64_t da, uint64_t db, int sc){
  asm volatile("{.reg .pred p; setp.ne.b32 p, %114, 0;\n wgmma.mma_async.sync.aligned.m64n224k16.f32.bf16.bf16 {%0,%1,%2,%3,%4,%5,%6,%7,%8,%9,%10,%11,%12,%13,%14,%15,%16,%17,%18,%19,%20,%21,%22,%23,%24,%25,%26,%27,%28,%29,%30,%31,%32,%33,%34,%35,%36,%37,%38,%39,%40,%41,%42,%43,%44,%45,%46,%47,%48,%49,%50,%51,%52,%53,%54,%55,%56,%57,%58,%59,%60,%61,%62,%63,%64,%65,%66,%67,%68,%69,%70,%71,%72,%73,%74,%75,%76,%77,%78,%79,%80,%81,%82,%83,%84,%85,%86,%87,%88,%89,%90,%91,%92,%93,%94,%95,%96,%97,%98,%99,%100,%101,%102,%103,%104,%105,%106,%107,%108,%109,%110,%111}, %112, %113, p, 1, 1, 0, 0;}"
   :"+f"(d[0]),"+f"(d[1]),"+f"(d[2]),"+f"(d[3]),"+f"(d[4]),"+f"(d[5]),"+f"(d[6]),"+f"(d[7]),"+f"(d[8]),"+f"(d[9]),"+f"(d[10]),"+f"(d[11]),"+f"(d[12]),"+f"(d[13]),"+f"(d[14]),"+f"(d[15]),"+f"(d[16]),"+f"(d[17]),"+f"(d[18]),"+f"(d[19]),"+f"(d[20]),"+f"(d[21]),"+f"(d[22]),"+f"(d[23]),"+f"(d[24]),"+f"(d[25]),"+f"(d[26]),"+f"(d[27]),"+f"(d[28]),"+f"(d[29]),"+f"(d[30]),"+f"(d[31]),"+f"(d[32]),"+f"(d[33]),"+f"(d[34]),"+f"(d[35]),"+f"(d[36]),"+f"(d[37]),"+f"(d[38]),"+f"(d[39]),"+f"(d[40]),"+f"(d[41]),"+f"(d[42]),"+f"(d[43]),"+f"(d[44]),"+f"(d[45]),"+f"(d[46]),"+f"(d[47]),"+f"(d[48]),"+f"(d[49]),"+f"(d[50]),"+f"(d[51]),"+f"(d[52]),"+f"(d[53]),"+f"(d[54]),"+f"(d[55]),"+f"(d[56]),"+f"(d[57]),"+f"(d[58]),"+f"(d[59]),"+f"(d[60]),"+f"(d[61]),"+f"(d[62]),"+f"(d[63]),"+f"(d[64]),"+f"(d[65]),"+f"(d[66]),"+f"(d[67]),"+f"(d[68]),"+f"(d[69]),"+f"(d[70]),"+f"(d[71]),"+f"(d[72]),"+f"(d[73]),"+f"(d[74]),"+f"(d[75]),"+f"(d[76]),"+f"(d[77]),"+f"(d[78]),"+f"(d[79]),"+f"(d[80]),"+f"(d[81]),"+f"(d[82]),"+f"(d[83]),"+f"(d[84]),"+f"(d[85]),"+f"(d[86]),"+f"(d[87]),"+f"(d[88]),"+f"(d[89]),"+f"(d[90]),"+f"(d[91]),"+f"(d[92]),"+f"(d[93]),"+f"(d[94]),"+f"(d[95]),"+f"(d[96]),"+f"(d[97]),"+f"(d[98]),"+f"(d[99]),"+f"(d[100]),"+f"(d[101]),"+f"(d[102]),"+f"(d[103]),"+f"(d[104]),"+f"(d[105]),"+f"(d[106]),"+f"(d[107]),"+f"(d[108]),"+f"(d[109]),"+f"(d[110]),"+f"(d[111])
   :"l"(da),"l"(db),"r"(sc));
}

__device__ __forceinline__ void wgmma224_ta(float (&d)[112], uint64_t da, uint64_t db, int sc){
  asm volatile("{.reg .pred p; setp.ne.b32 p, %114, 0;\n wgmma.mma_async.sync.aligned.m64n224k16.f32.bf16.bf16 {%0,%1,%2,%3,%4,%5,%6,%7,%8,%9,%10,%11,%12,%13,%14,%15,%16,%17,%18,%19,%20,%21,%22,%23,%24,%25,%26,%27,%28,%29,%30,%31,%32,%33,%34,%35,%36,%37,%38,%39,%40,%41,%42,%43,%44,%45,%46,%47,%48,%49,%50,%51,%52,%53,%54,%55,%56,%57,%58,%59,%60,%61,%62,%63,%64,%65,%66,%67,%68,%69,%70,%71,%72,%73,%74,%75,%76,%77,%78,%79,%80,%81,%82,%83,%84,%85,%86,%87,%88,%89,%90,%91,%92,%93,%94,%95,%96,%97,%98,%99,%100,%101,%102,%103,%104,%105,%106,%107,%108,%109,%110,%111}, %112, %113, p, 1, 1, 1, 0;}"
   :"+f"(d[0]),"+f"(d[1]),"+f"(d[2]),"+f"(d[3]),"+f"(d[4]),"+f"(d[5]),"+f"(d[6]),"+f"(d[7]),"+f"(d[8]),"+f"(d[9]),"+f"(d[10]),"+f"(d[11]),"+f"(d[12]),"+f"(d[13]),"+f"(d[14]),"+f"(d[15]),"+f"(d[16]),"+f"(d[17]),"+f"(d[18]),"+f"(d[19]),"+f"(d[20]),"+f"(d[21]),"+f"(d[22]),"+f"(d[23]),"+f"(d[24]),"+f"(d[25]),"+f"(d[26]),"+f"(d[27]),"+f"(d[28]),"+f"(d[29]),"+f"(d[30]),"+f"(d[31]),"+f"(d[32]),"+f"(d[33]),"+f"(d[34]),"+f"(d[35]),"+f"(d[36]),"+f"(d[37]),"+f"(d[38]),"+f"(d[39]),"+f"(d[40]),"+f"(d[41]),"+f"(d[42]),"+f"(d[43]),"+f"(d[44]),"+f"(d[45]),"+f"(d[46]),"+f"(d[47]),"+f"(d[48]),"+f"(d[49]),"+f"(d[50]),"+f"(d[51]),"+f"(d[52]),"+f"(d[53]),"+f"(d[54]),"+f"(d[55]),"+f"(d[56]),"+f"(d[57]),"+f"(d[58]),"+f"(d[59]),"+f"(d[60]),"+f"(d[61]),"+f"(d[62]),"+f"(d[63]),"+f"(d[64]),"+f"(d[65]),"+f"(d[66]),"+f"(d[67]),"+f"(d[68]),"+f"(d[69]),"+f"(d[70]),"+f"(d[71]),"+f"(d[72]),"+f"(d[73]),"+f"(d[74]),"+f"(d[75]),"+f"(d[76]),"+f"(d[77]),"+f"(d[78]),"+f"(d[79]),"+f"(d[80]),"+f"(d[81]),"+f"(d[82]),"+f"(d[83]),"+f"(d[84]),"+f"(d[85]),"+f"(d[86]),"+f"(d[87]),"+f"(d[88]),"+f"(d[89]),"+f"(d[90]),"+f"(d[91]),"+f"(d[92]),"+f"(d[93]),"+f"(d[94]),"+f"(d[95]),"+f"(d[96]),"+f"(d[97]),"+f"(d[98]),"+f"(d[99]),"+f"(d[100]),"+f"(d[101]),"+f"(d[102]),"+f"(d[103]),"+f"(d[104]),"+f"(d[105]),"+f"(d[106]),"+f"(d[107]),"+f"(d[108]),"+f"(d[109]),"+f"(d[110]),"+f"(d[111])
   :"l"(da),"l"(db),"r"(sc));
}

struct Params {
  CUtensorMap tq, tk, tv, to, tx128, tx32;
  const bf16 *x, *mem0, *wr, *wgate, *wup, *wdown, *gatew;
  bf16* out;
};

constexpr uint32_t G_BAR = 229376;
constexpr uint32_t PB_F = G_BAR + 320;

__device__ __forceinline__ void gate_rows(const Params& P, Flags* F, int blk, int lane) {
  const int r = lane >> 2, p = lane & 3;
  const uint4* x0 = reinterpret_cast<const uint4*>(P.x + (size_t)(blk * 16 + r) * DM) + p;
  const uint4* wv = reinterpret_cast<const uint4*>(r == 0 ? P.wr : P.gatew) + p;
  float c[4] = {0.f, 0.f, 0.f, 0.f};
#pragma unroll 1
  for (int j = 0; j < 14; j++) {
    const uint4 a = __ldg(x0 + j * 4), b = __ldg(x0 + 8 * (DM / 8) + j * 4), w = __ldg(wv + j * 4);
    mma(c, a.x, b.x, a.y, b.y, w.x, w.y);
    mma(c, a.z, b.z, a.w, b.w, w.z, w.w);
  }
  if (p == 0) {
    g_r[blk * 16 + r] = rbf(c[0]);
    g_r[blk * 16 + 8 + r] = rbf(c[2]);
    g_gate[blk * 16 + r] = rbf(1.f / (1.f + __expf(-rbf(c[1]))));
    g_gate[blk * 16 + 8 + r] = rbf(1.f / (1.f + __expf(-rbf(c[3]))));
  }
  __syncwarp();
  if (lane == 0) { fence_gpu(); red_add(&F->fx, 1); }
}

__device__ __forceinline__ void phase_w_load_m(const Params& P, int mat, int mb, int kq, uint32_t dst, uint32_t bar) {
  if (mat < 16) tma2d(dst, &P.tq, mat * DH + kq * 64, mb * 64, bar);
  else tma2d(dst, &P.to, mb * 64, (mat - 16) * DH + kq * 64, bar);
}

__device__ __forceinline__ void phase_w(const Params& P, Flags* F, int item, uint32_t sb, uint32_t par) {
  const int tid = read_tid(), warp = tid >> 5, lane = tid & 31, wg = warp >> 2, w4 = warp & 3;
  const int mat = (item & 63) >> 1, ch = item & 1, mg = item >> 6;
  const uint32_t nbuf = sb, mbuf = sb + 114688;
  if (tid == 0) {
    const CUtensorMap* tn = mat < 16 ? &P.tk : &P.tv;
    for (int kq = 0; kq < 4; kq++) {
      mbar_expect(sb + PB_F + 8 * kq, 28672 + 8192);
      tma2d(nbuf + kq * 28672, tn, (mat & 15) * DH + kq * 64, ch * 224, sb + PB_F + 8 * kq);
      phase_w_load_m(P, mat, mg * 4, kq, mbuf + kq * 8192, sb + PB_F + 8 * kq);
    }
    for (int b = 1; b < 4; b++) {
      const int nk = b < 3 ? 4 : (mg == 0 ? 2 : 0);
      mbar_expect(sb + PB_F + 8 * (3 + b), nk * 8192);
      for (int kq = 0; kq < nk; kq++) phase_w_load_m(P, mat, mg * 4 + b, kq, mbuf + (b * 4 + kq) * 8192, sb + PB_F + 8 * (3 + b));
    }
    if (mg) mbar_arrive(sb + PB_F + 8 * 7);
  }
  __syncwarp();
  float d[112];
  const float sc = mat < 16 ? 0.0625f * 1.4426950408889634f : 1.f;
  const int npass = (mg == 0 && wg == 0) ? 2 : 1;
#pragma unroll 1
  for (int pass = 0; pass < npass; pass++) {
    const int blk = pass ? 3 : wg;
    if (blk) mbar_wait(sb + PB_F + 8 * (3 + blk), par);
#pragma unroll 1
    for (int kq = 0; kq < 4; kq++) {
      mbar_wait(sb + PB_F + 8 * kq, par);
      if (pass && kq == 2) mbar_wait(sb + PB_F + 8 * 7, par);
      const uint32_t ma = mbuf + ((pass && kq >= 2) ? kq - 2 : blk * 4 + kq) * 8192;
      const uint64_t da = mkdesc_sw(ma), db = mkdesc_sw(nbuf + kq * 28672);
      if (mat >= 16) {
        wg_fence();
#pragma unroll
        for (int ks = 0; ks < 4; ks++) wgmma224_ta(d, da + ks * 128, db + ks * 2, kq | ks);
        wg_commit();
      } else {
        wg_fence();
#pragma unroll
        for (int ks = 0; ks < 4; ks++) wgmma224(d, da + ks * 2, db + ks * 2, kq | ks);
        wg_commit();
      }
    }
    wg_wait<0>();
    if (npass == 2 && pass == 0) {
      bar_sync(1, 128);
      if (tid == 0) {
        mbar_expect(sb + PB_F + 8 * 7, 16384);
        phase_w_load_m(P, mat, 3, 2, mbuf, sb + PB_F + 8 * 7);
        phase_w_load_m(P, mat, 3, 3, mbuf + 8192, sb + PB_F + 8 * 7);
      }
      __syncwarp();
    }
    const int RB = (mg * 4 + blk) * 8 + w4 * 2, hf = RB >= 28;
    uint32_t* wc = reinterpret_cast<uint32_t*>(g_WC) + ((mat * 2 + hf) * 7 * 28 + (RB - hf * 28)) * 256 + lane;
#pragma unroll
    for (int jg = 0; jg < 7; jg++) {
      const int G = jg + ch * 7;
      uint32_t* o = wc + (G >> 1) * 7168 + (G & 1) * 128;
#pragma unroll
      for (int j = 0; j < 4; j++) {
        o[j * 32] = pack2(d[(jg * 4 + j) * 4] * sc, d[(jg * 4 + j) * 4 + 1] * sc);
        o[j * 32 + 256] = pack2(d[(jg * 4 + j) * 4 + 2] * sc, d[(jg * 4 + j) * 4 + 3] * sc);
      }
    }
    warp_publish(&F->fw[mat], lane);
  }
}

constexpr int NGEMM_ITEMS = 256;
constexpr uint32_t G_X = 0, G_W = 114688;
constexpr uint32_t GB_WFULL = G_BAR, GB_WEMPTY = G_BAR + 32, GB_XFULL = G_BAR + 64, GB_XEMPTY = G_BAR + 128,
                   GB_ITEM = G_BAR + 192, G_ITEMBUF = G_BAR + 224, G_MISC = G_BAR + 256, GB_PUB = G_BAR + 272;

__device__ __forceinline__ void gemm_init_barriers(uint32_t sb) {
  for (int i = 0; i < 4; i++) { mbar_init(sb + GB_WFULL + 8 * i, 1); mbar_init(sb + GB_WEMPTY + 8 * i, 16); mbar_init(sb + GB_ITEM + 8 * i, 1); }
  for (int i = 0; i < 7; i++) { mbar_init(sb + GB_XFULL + 8 * i, 1); mbar_init(sb + GB_XEMPTY + 8 * i, 8); }
  for (int i = 0; i < 8; i++) mbar_init(sb + PB_F + 8 * i, 1);
  mbar_init(sb + GB_PUB, 8); mbar_init(sb + GB_PUB + 8, 8);
  asm volatile("fence.mbarrier_init.release.cluster;" ::: "memory");
}

__device__ __forceinline__ uint32_t lds32(uint32_t a) { uint32_t v; asm volatile("ld.shared.u32 %0, [%1];" : "=r"(v) : "r"(a) : "memory"); return v; }

__device__ __forceinline__ void gemm_producer(const Params& P, Flags* F, uint32_t sb, uint32_t crank) {
  const uint32_t odd = crank & 1, peer = crank ^ 1;
  const uint16_t mask = (uint16_t)(3u << (crank & ~1u));
  uint32_t st = 0, ph = 1;
  unsigned next = 0;
  if (!odd) next = atomicAdd(&F->q_gemm, 1);
  for (int n = 0;; n++) {
    unsigned item;
    const uint32_t ib = (n & 3);
    if (!odd) {
      item = next;
      sts32(sb + G_ITEMBUF + 4 * ib, item);
      asm volatile("st.shared::cluster.u32 [%0], %1;" ::"r"(mapa(sb + G_ITEMBUF + 4 * ib, peer)), "r"(item) : "memory");
      mbar_arrive(sb + GB_ITEM + 8 * ib);
      mbar_arrive_cluster(mapa(sb + GB_ITEM + 8 * ib, peer));
      if (item < NGEMM_ITEMS) next = atomicAdd(&F->q_gemm, 1);
    } else {
      mbar_wait(sb + GB_ITEM + 8 * ib, (n >> 2) & 1);
      item = lds32(sb + G_ITEMBUF + 4 * ib);
    }
    if (item >= NGEMM_ITEMS) break;
    const int tile = (item >> 5) * 2 + odd, mat = item & 31;
    const char* wsrc = reinterpret_cast<const char*>(g_WC) + (size_t)mat * 401408 + odd * 14336;
    for (int i = 0; i < 14; i++) {
      if (i < 7) {
        mbar_wait(sb + GB_XEMPTY + 8 * i, (n & 1) ^ 1);
        mbar_expect(sb + GB_XFULL + 8 * i, 16384);
        tma2d(sb + G_X + i * 16384, &P.tx128, i * 64, tile * 128, sb + GB_XFULL + 8 * i);
      }
      if (i == 0) flag_wait(&F->fw[mat], 56);
      mbar_wait(sb + GB_WEMPTY + 8 * st, ph);
      mbar_expect(sb + GB_WFULL + 8 * st, 28672);
      bulk_g2s_mc(sb + G_W + st * 28672 + odd * 14336, wsrc + (size_t)i * 28672, 14336, sb + GB_WFULL + 8 * st, mask);
      if (++st == 4) { st = 0; ph ^= 1; }
    }
  }
}

__device__ __forceinline__ void stg128(void* p, uint32_t a, uint32_t b, uint32_t c, uint32_t d) { asm volatile("st.global.v4.u32 [%0], {%1,%2,%3,%4};" ::"l"(p), "r"(a), "r"(b), "r"(c), "r"(d) : "memory"); }
__device__ __forceinline__ void stg64(void* p, uint32_t a, uint32_t b) { asm volatile("st.global.v2.u32 [%0], {%1,%2};" ::"l"(p), "r"(a), "r"(b) : "memory"); }

__device__ __forceinline__ void gemm_epi_k(const float (&d)[112], uint32_t sb, int tile, int head, int ch, int t16, int lane) {
  const int seg = tile * 4 + (t16 >> 1), tok16 = t16 & 1;
  float sacc[2][2][4];
#pragma unroll
  for (int a = 0; a < 2; a++)
#pragma unroll
    for (int b = 0; b < 2; b++)
#pragma unroll
      for (int c = 0; c < 4; c++) sacc[a][b][c] = 0.f;
  const uint32_t xa = sb + G_X + (t16 >> 1) * 4096 + (lane & 15) * 128, xs = ((lane >> 4) ^ (lane & 7)) << 4;
  char* dst = reinterpret_cast<char*>(g_KAF) + (size_t)((seg * 16 + head) * 4 + ch * 2) * 7168 + tok16 * 3584 + lane * 16;
  uint32_t pb[4];
#pragma unroll
  for (int k = 0; k < 14; k++) {
    const uint32_t b00 = pack2(d[8 * k + 0], d[8 * k + 1]), b01 = pack2(d[8 * k + 4], d[8 * k + 5]);
    const uint32_t b10 = pack2(d[8 * k + 2], d[8 * k + 3]), b11 = pack2(d[8 * k + 6], d[8 * k + 7]);
    {
      char* o = dst + (k / 7) * 7168 + ((k % 7) >> 1) * 512;
      if (k % 7 == 6) {
        stg64(o - lane * 8, b00, b01);
        stg64(o + 1792 - lane * 8, b10, b11);
      } else if ((k % 7) & 1) {
        stg128(o, pb[0], b00, pb[1], b01);
        stg128(o + 1792, pb[2], b10, pb[3], b11);
      } else { pb[0] = b00; pb[1] = b01; pb[2] = b10; pb[3] = b11; }
    }
    const int kc = (ch * 14 + k) * 2;
    const uint32_t ka = xa + (kc >> 3) * 16384 + (((kc & 7) << 4) ^ xs);
    uint32_t a0, a1, a2, a3;
    ldsm4(a0, a1, a2, a3, ka + 2048);
    mma(sacc[1][0], a0, a1, a2, a3, b00, b01);
    mma(sacc[1][1], a0, a1, a2, a3, b10, b11);
    if (tok16 == 0) {
      ldsm4(a0, a1, a2, a3, ka);
      mma(sacc[0][0], a0, a1, a2, a3, b00, b01);
      mma(sacc[0][1], a0, a1, a2, a3, b10, b11);
    }
  }
  float4* sx = g_SXX + (size_t)((seg * 16 + head) * 2 + ch) * 8 * 32 + tok16 * 2 * 32 + lane;
#pragma unroll
  for (int b = 0; b < 2; b++) {
    sx[(4 + b) * 32] = make_float4(sacc[1][b][0], sacc[1][b][1], sacc[1][b][2], sacc[1][b][3]);
    if (tok16 == 0) sx[b * 32] = make_float4(sacc[0][b][0], sacc[0][b][1], sacc[0][b][2], sacc[0][b][3]);
  }
}

__device__ __forceinline__ void gemm_epi_v(const float (&d)[112], int tile, int head, int ch, int t16, int lane) {
  const int seg = tile * 4 + (t16 >> 1), tok16 = t16 & 1;
  uint4* dst = g_VBF + ((size_t)((seg * 16 + head) * 28 + ch * 14) * 2 + tok16) * 32 + lane;
#pragma unroll
  for (int j = 0; j < 14; j++) {
    const uint32_t a0 = movm(pack2(d[8 * j + 0], d[8 * j + 1])), a1 = movm(pack2(d[8 * j + 4], d[8 * j + 5]));
    const uint32_t a2 = movm(pack2(d[8 * j + 2], d[8 * j + 3])), a3 = movm(pack2(d[8 * j + 6], d[8 * j + 7]));
    dst[j * 64] = make_uint4(a0, a1, a2, a3);
  }
}

__device__ __forceinline__ void gemm_consumer(Flags* F, uint32_t sb, uint32_t crank, int cta) {
  const int tid = read_tid(), warp = tid >> 5, lane = tid & 31, wg = warp >> 2;
  const uint32_t odd = crank & 1;
  const uint32_t rel = mapa(sb + GB_WEMPTY, lane == 0 ? crank : (crank ^ 1));
  uint32_t st = 0, ph = 0;
  float d[112];
  for (int n = 0;; n++) {
    mbar_wait(sb + GB_ITEM + 8 * (n & 3), (n >> 2) & 1);
    const unsigned item = lds32(sb + G_ITEMBUF + 4 * (n & 3));
    if (item >= NGEMM_ITEMS) break;
    const int tile = (item >> 5) * 2 + odd, mat = item & 31;
    if (read_tid() == 0 && n < 24) PROF_CTA(cta, 8 + n);
    for (int ch = 0; ch < 2; ch++) {
      uint32_t pst = 0;
      for (int kb = 0; kb < 7; kb++) {
        if (ch == 0) mbar_wait(sb + GB_XFULL + 8 * kb, n & 1);
        mbar_wait(sb + GB_WFULL + 8 * st, ph);
        wg_fence();
#pragma unroll
        for (int ks = 0; ks < 4; ks++) {
          const uint64_t da = mkdesc_sw(sb + G_X + kb * 16384 + wg * 8192 + ks * 32);
          const uint64_t db = mkdesc(sb + G_W + st * 28672 + ks * 256, 128, 1024);
          wgmma224(d, da, db, kb | ks);
        }
        wg_commit();
        if (kb > 0) {
          wg_wait<1>();
          if (lane < 2) asm volatile("mbarrier.arrive.shared::cluster.b64 _, [%0];" ::"r"(rel + 8 * pst) : "memory");
          if (ch == 1 && lane == 0 && (mat >= 16 || kb - 1 < 3)) mbar_arrive(sb + GB_XEMPTY + 8 * (kb - 1));
        }
        pst = st;
        if (++st == 4) { st = 0; ph ^= 1; }
      }
      wg_wait<0>();
      if (lane < 2) asm volatile("mbarrier.arrive.shared::cluster.b64 _, [%0];" ::"r"(rel + 8 * pst) : "memory");
      if (mat < 16) {
        gemm_epi_k(d, sb, tile, mat, ch, warp, lane);
        if (ch == 1) { __syncwarp(); if (lane >= 3 && lane < 7) mbar_arrive(sb + GB_XEMPTY + 8 * lane); }
      } else {
        if (ch == 1 && lane == 0) mbar_arrive(sb + GB_XEMPTY + 8 * 6);
        gemm_epi_v(d, tile, mat - 16, ch, warp, lane);
      }
      __syncwarp();
      if (lane == 0) mbar_arrive(sb + GB_PUB + 8 * ch);
    }
  }
}

__device__ __forceinline__ void gemm_publisher(Flags* F, uint32_t sb, uint32_t crank, int lane) {
  for (int n = 0;; n++) {
    mbar_wait(sb + GB_ITEM + 8 * (n & 3), (n >> 2) & 1);
    const unsigned item = lds32(sb + G_ITEMBUF + 4 * (n & 3));
    if (item >= NGEMM_ITEMS) break;
    const int tile = (item >> 5) * 2 + (crank & 1);
    for (int ch = 0; ch < 2; ch++) {
      mbar_wait(sb + GB_PUB + 8 * ch, n & 1);
      fence_async_all();
      fence_gpu();
      if (lane < 4) red_add(&F->fkv[(tile * 4 + lane) * 8 + ((item & 15) >> 1)], 1);
    }
  }
}

constexpr int NFFN_ITEMS = 28;

__device__ __forceinline__ int find_sel(Flags* F, float* sm) {
  const int tid = read_tid(), lane = tid & 31, warp = tid >> 5;
  if (tid == 0) flag_wait(&F->fx, 128);
  bar_sync(2, 256);
  float bv = -INFINITY; int bi = 0x7fffffff;
#pragma unroll
  for (int j = 0; j < 8; j++) {
    const int i = j * 256 + tid;
    const float v = __ldcg(&g_r[i]);
    if (v > bv || bi == 0x7fffffff) { bv = v; bi = i; }
  }
#pragma unroll
  for (int o = 16; o; o >>= 1) {
    const float ov = __shfl_xor_sync(0xffffffffu, bv, o); const int oi = __shfl_xor_sync(0xffffffffu, bi, o);
    if (ov > bv || (ov == bv && oi < bi)) { bv = ov; bi = oi; }
  }
  if (lane == 0) { sm[warp] = bv; sm[8 + warp] = __int_as_float(bi); }
  bar_sync(2, 256);
  bv = sm[0]; bi = __float_as_int(sm[8]);
#pragma unroll
  for (int w = 1; w < 8; w++) {
    const float ov = sm[w]; const int oi = __float_as_int(sm[8 + w]);
    if (ov > bv || (ov == bv && oi < bi)) { bv = ov; bi = oi; }
  }
  bar_sync(2, 256);
  return bi;
}

__device__ __forceinline__ void ffn_item(const Params& P, Flags* F, int it, float* sm) {
  const int tid = read_tid(), lane = tid & 31, warp = tid >> 5;
  const int sel = find_sel(F, sm);
  float* xs = sm;
  float* red = sm + 512;
  float* hid = sm + 2560;
  for (int i = tid; i < DM; i += 256) xs[i] = __bfloat162float(P.x[(size_t)sel * DM + i]);
  bar_sync(2, 256);
  {
    const int chunk = lane & 7, dg = warp * 4 + (lane >> 3);
    float ag[8], au[8];
#pragma unroll
    for (int i = 0; i < 8; i++) ag[i] = au[i] = 0.f;
    uint4 wg[14], wu[14];
#pragma unroll
    for (int j = 0; j < 14; j++) {
      const size_t off = (size_t)(dg * 14 + j) * FF + it * 64 + chunk * 8;
      wg[j] = __ldg(reinterpret_cast<const uint4*>(P.wgate + off));
      wu[j] = __ldg(reinterpret_cast<const uint4*>(P.wup + off));
    }
#pragma unroll
    for (int j = 0; j < 14; j++) {
      const float xv = xs[dg * 14 + j];
      const uint32_t a[4] = {wg[j].x, wg[j].y, wg[j].z, wg[j].w}, b[4] = {wu[j].x, wu[j].y, wu[j].z, wu[j].w};
#pragma unroll
      for (int i = 0; i < 4; i++) {
        ag[2 * i] = fmaf(xv, bf_lo(a[i]), ag[2 * i]); ag[2 * i + 1] = fmaf(xv, bf_hi(a[i]), ag[2 * i + 1]);
        au[2 * i] = fmaf(xv, bf_lo(b[i]), au[2 * i]); au[2 * i + 1] = fmaf(xv, bf_hi(b[i]), au[2 * i + 1]);
      }
    }
#pragma unroll
    for (int i = 0; i < 8; i++) {
      ag[i] += __shfl_xor_sync(0xffffffffu, ag[i], 8); ag[i] += __shfl_xor_sync(0xffffffffu, ag[i], 16);
      au[i] += __shfl_xor_sync(0xffffffffu, au[i], 8); au[i] += __shfl_xor_sync(0xffffffffu, au[i], 16);
    }
    if (lane < 8) {
#pragma unroll
      for (int i = 0; i < 8; i++) { red[warp * 128 + chunk * 8 + i] = ag[i]; red[warp * 128 + 64 + chunk * 8 + i] = au[i]; }
    }
  }
  bar_sync(2, 256);
  if (tid < 64) {
    float g = 0.f, u = 0.f;
#pragma unroll
    for (int w = 0; w < 8; w++) { g += red[w * 128 + tid]; u += red[w * 128 + 64 + tid]; }
    g = rbf(g); u = rbf(u);
    const float sg = rbf(g / (1.f + __expf(-g)));
    hid[tid] = rbf(sg * u);
  }
  bar_sync(2, 256);
  if (tid < 224) {
    const int chunk = tid % 56, fg = tid / 56;
    float ay[8];
#pragma unroll
    for (int i = 0; i < 8; i++) ay[i] = 0.f;
    uint4 wd[16];
#pragma unroll
    for (int j = 0; j < 16; j++) wd[j] = __ldg(reinterpret_cast<const uint4*>(P.wdown + (size_t)(it * 64 + fg * 16 + j) * DM + chunk * 8));
#pragma unroll
    for (int j = 0; j < 16; j++) {
      const float hv = hid[fg * 16 + j];
      const uint32_t a[4] = {wd[j].x, wd[j].y, wd[j].z, wd[j].w};
#pragma unroll
      for (int i = 0; i < 4; i++) { ay[2 * i] = fmaf(hv, bf_lo(a[i]), ay[2 * i]); ay[2 * i + 1] = fmaf(hv, bf_hi(a[i]), ay[2 * i + 1]); }
    }
#pragma unroll
    for (int i = 0; i < 8; i++) red[fg * DM + chunk * 8 + i] = ay[i];
  }
  bar_sync(2, 256);
  for (int i = tid; i < DM; i += 256) g_ypart[it * DM + i] = red[i] + red[DM + i] + red[2 * DM + i] + red[3 * DM + i];
  if (it == 0 && tid == 0) g_sel = sel;
  bar_sync(2, 256);
  if (tid == 0) { fence_gpu(); red_add(&F->fffn, 1); }
}

__device__ __forceinline__ float4 ldcg4f(const float4* p) { return __ldcg(p); }

__device__ __forceinline__ void attn_item(const Params& P, Flags* F, int seg, uint32_t sb, float* ysm) {
  const int tid = read_tid(), lane = tid & 31, warp = tid >> 5, r = lane >> 2, p = lane & 3;
  if (tid == 0) flag_wait(&F->fseg[seg], 64);
  if (tid == 32) flag_wait(&F->fffn, NFFN_ITEMS);
  bar_sync(2, 256);
  uint32_t pm[2][2][2];
#pragma unroll
  for (int hd = 0; hd < 2; hd++) {
    const int head = warp * 2 + hd;
    const float4* sx = g_SXX + (size_t)(seg * 16 + head) * 2 * 8 * 32 + lane;
    const float4* sm = g_SXM + (size_t)(seg * 16 + head) * 4 * 2 * 32 + lane;
#pragma unroll
    for (int mt = 0; mt < 2; mt++) {
      constexpr int dummy = 0; (void)dummy;
      const int NT = mt == 0 ? 2 : 4;
      float s[4][4], m4[4];
#pragma unroll
      for (int nt = 0; nt < 4; nt++) if (nt < NT) {
        const float4 a = ldcg4f(sx + (mt * 4 + nt) * 32), b = ldcg4f(sx + (8 + mt * 4 + nt) * 32);
        s[nt][0] = a.x + b.x; s[nt][1] = a.y + b.y; s[nt][2] = a.z + b.z; s[nt][3] = a.w + b.w;
      }
      {
        const float4 a = ldcg4f(sm + mt * 32), b = ldcg4f(sm + (2 + mt) * 32), c = ldcg4f(sm + (4 + mt) * 32), d = ldcg4f(sm + (6 + mt) * 32);
        m4[0] = (a.x + b.x) + (c.x + d.x); m4[1] = (a.y + b.y) + (c.y + d.y); m4[2] = (a.z + b.z) + (c.z + d.z); m4[3] = (a.w + b.w) + (c.w + d.w);
      }
      {
        const int n0 = mt * 2;
        if (2 * p > r) { s[n0][0] = -INFINITY; s[n0 + 1][2] = -INFINITY; }
        if (2 * p + 1 > r) { s[n0][1] = -INFINITY; s[n0 + 1][3] = -INFINITY; }
        s[n0 + 1][0] = -INFINITY; s[n0 + 1][1] = -INFINITY;
      }
      float mx0 = fmaxf(m4[0], m4[1]), mx1 = fmaxf(m4[2], m4[3]);
#pragma unroll
      for (int nt = 0; nt < 4; nt++) if (nt < NT) { mx0 = fmaxf(mx0, fmaxf(s[nt][0], s[nt][1])); mx1 = fmaxf(mx1, fmaxf(s[nt][2], s[nt][3])); }
      mx0 = fmaxf(mx0, __shfl_xor_sync(0xffffffffu, mx0, 1)); mx0 = fmaxf(mx0, __shfl_xor_sync(0xffffffffu, mx0, 2));
      mx1 = fmaxf(mx1, __shfl_xor_sync(0xffffffffu, mx1, 1)); mx1 = fmaxf(mx1, __shfl_xor_sync(0xffffffffu, mx1, 2));
      m4[0] = ex2(m4[0] - mx0); m4[1] = ex2(m4[1] - mx0); m4[2] = ex2(m4[2] - mx1); m4[3] = ex2(m4[3] - mx1);
      float l0 = m4[0] + m4[1], l1 = m4[2] + m4[3];
#pragma unroll
      for (int nt = 0; nt < 4; nt++) if (nt < NT) {
        s[nt][0] = ex2(s[nt][0] - mx0); s[nt][1] = ex2(s[nt][1] - mx0); s[nt][2] = ex2(s[nt][2] - mx1); s[nt][3] = ex2(s[nt][3] - mx1);
        l0 += s[nt][0] + s[nt][1]; l1 += s[nt][2] + s[nt][3];
      }
      l0 += __shfl_xor_sync(0xffffffffu, l0, 1); l0 += __shfl_xor_sync(0xffffffffu, l0, 2);
      l1 += __shfl_xor_sync(0xffffffffu, l1, 1); l1 += __shfl_xor_sync(0xffffffffu, l1, 2);
      const float i0 = 1.f / l0, i1 = 1.f / l1;
      pm[hd][mt][0] = pack2(m4[0] * i0, m4[1] * i0); pm[hd][mt][1] = pack2(m4[2] * i1, m4[3] * i1);
#pragma unroll
      for (int kt = 0; kt < 2; kt++) if (2 * kt < NT) {
        sts128(sb + (((warp * 5 + hd * 2 + kt) * 2 + mt) * 32 + lane) * 16,
               pack2(s[2 * kt][0] * i0, s[2 * kt][1] * i0), pack2(s[2 * kt + 1][0] * i0, s[2 * kt + 1][1] * i0),
               pack2(s[2 * kt][2] * i1, s[2 * kt][3] * i1), pack2(s[2 * kt + 1][2] * i1, s[2 * kt + 1][3] * i1));
      }
    }
  }
#pragma unroll
  for (int mt = 0; mt < 2; mt++)
    sts128(sb + (((warp * 5 + 4) * 2 + mt) * 32 + lane) * 16, pm[0][mt][0], pm[1][mt][0], pm[0][mt][1], pm[1][mt][1]);
  const int sel = __ldcg(&g_sel);
  if ((sel >> 5) == seg) {
    const float rs = rbf(1.f / (1.f + __expf(-__ldcg(&g_r[sel]))));
    for (int i = tid; i < DM; i += 256) {
      float y = 0.f;
      for (int k = 0; k < NFFN_ITEMS; k++) y += __ldcg(&g_ypart[k * DM + i]);
      ysm[i] = rbf(rbf(y) * rs);
    }
  }
  bar_sync(2, 256);
  if (warp < 7) {
    float acc[4][4][4];
#pragma unroll
    for (int a = 0; a < 4; a++)
#pragma unroll
      for (int b = 0; b < 4; b++)
#pragma unroll
        for (int c = 0; c < 4; c++) acc[a][b][c] = 0.f;
    const uint4* vb = g_VBF + ((size_t)seg * 16 * 28 + warp * 4) * 64 + lane;
    const uint4* uf = g_UF + ((size_t)seg * 8 * 28 + warp * 4) * 32 + lane;
    uint4 A[5][4];
#pragma unroll
    for (int j = 0; j < 5; j++)
#pragma unroll
      for (int n = 0; n < 4; n++) A[j][n] = j < 4 ? __ldcg(vb + ((j >> 1) * 28 + n) * 64 + (j & 1) * 32) : __ldcg(uf + n * 32);
#pragma unroll 1
    for (int g = 0; g < 8; g++) {
      const int gn = g < 7 ? g + 1 : g;
#pragma unroll
      for (int j = 0; j < 5; j++) {
        const uint4 b1 = lds128(sb + (((g * 5 + j) * 2 + 1) * 32 + lane) * 16);
        if (j != 1 && j != 3) {
          const uint4 b0 = lds128(sb + (((g * 5 + j) * 2) * 32 + lane) * 16);
#pragma unroll
          for (int n = 0; n < 4; n++) {
            mma(acc[n][0], A[j][n].x, A[j][n].y, A[j][n].z, A[j][n].w, b0.x, b0.y);
            mma(acc[n][1], A[j][n].x, A[j][n].y, A[j][n].z, A[j][n].w, b0.z, b0.w);
          }
        }
#pragma unroll
        for (int n = 0; n < 4; n++) {
          mma(acc[n][2], A[j][n].x, A[j][n].y, A[j][n].z, A[j][n].w, b1.x, b1.y);
          mma(acc[n][3], A[j][n].x, A[j][n].y, A[j][n].z, A[j][n].w, b1.z, b1.w);
        }
#pragma unroll
        for (int n = 0; n < 4; n++)
          A[j][n] = j < 4 ? __ldcg(vb + ((gn * 2 + (j >> 1)) * 28 + n) * 64 + (j & 1) * 32) : __ldcg(uf + (gn * 28 + n) * 32);
      }
    }
#pragma unroll
    for (int tt = 0; tt < 4; tt++) {
      const int tok = seg * 32 + tt * 8 + r;
      const float g = __ldcg(&g_gate[tok]), og = rbf(1.f - g);
      const uint32_t* xr = reinterpret_cast<const uint32_t*>(P.x + (size_t)tok * DM) + warp * 32 + p;
      uint32_t* orow = reinterpret_cast<uint32_t*>(P.out + (size_t)tok * DM) + warp * 32 + p;
#pragma unroll
      for (int n = 0; n < 4; n++)
#pragma unroll
        for (int u = 0; u < 2; u++) {
          const uint32_t aw = movm(pack2(acc[n][tt][2 * u], acc[n][tt][2 * u + 1]));
          const uint32_t xw = __ldg(xr + n * 8 + u * 4);
          float b0 = bf_lo(xw), b1 = bf_hi(xw);
          if (tok == sel) { const int c = warp * 64 + n * 16 + u * 8 + 2 * p; b0 = rbf(b0 + ysm[c]); b1 = rbf(b1 + ysm[c + 1]); }
          orow[n * 8 + u * 4] = pack2(rbf(g * bf_lo(aw)) + rbf(og * b0), rbf(g * bf_hi(aw)) + rbf(og * b1));
        }
    }
  }
  bar_sync(2, 256);
}

__device__ __forceinline__ void tail_worker(const Params& P, Flags* F, uint32_t sb, char* smem, int cta) {
  int n = 0;
  volatile unsigned* slot = reinterpret_cast<volatile unsigned*>(smem + G_MISC);
  for (;;) {
    bar_sync(2, 256);
    if (read_tid() == 0) *slot = atomicAdd(&F->q_tail, 1);
    bar_sync(2, 256);
    const unsigned it = *slot;
    if (read_tid() == 0 && n < 16) PROF_CTA(cta, 32 + n);
    n++;
    if (it >= NFFN_ITEMS + NSEG) break;
    if (it < NFFN_ITEMS) ffn_item(P, F, it, reinterpret_cast<float*>(smem));
    else attn_item(P, F, it - NFFN_ITEMS, sb, reinterpret_cast<float*>(smem + 65536));
  }
}

#define POLL_DELAY_B 450
#define POLL_DELAY_C 200
constexpr uint32_t R_MEMT = 0, R_SX = 14336, R_SM = 22528, R_AR1 = 26624, R_AR2 = 27648, R_UFR = 31744,
                   R_BW = 33792  , R_STG = 76800, STG_BYTES = 44032, STG_KA = 28672, STG_VB = 35840,
                   R_AW = 208896;
constexpr uint32_t RB_C1 = G_BAR + 512, RB_SX = RB_C1 + 16, RB_SM = RB_C1 + 32, RB_STG = RB_C1 + 48, RB_EXP = RB_C1 + 72, RB_FW = RB_C1 + 88,
                   R_NEAR = RB_C1 + 96;
constexpr int BAR_LOC = 1, BAR_A = 3, BAR_W = 5, BAR_AB = 6  , BAR_FW = 10;
constexpr int LOC_COUNT = 352;
#define EXP_DELAY 200
#define LAND_DELAY 60
#define U_DELAY 40
#define PROBE_REPS 4
#define B_RING 10
#define SAFE_RANGE 40.f

__device__ __forceinline__ const uint4* wc_row(int mat, int RB, int KC, int r) {
  const int hf = RB >= 28;
  return g_WC + ((((mat * 2 + hf) * 7 + (KC >> 3)) * 28 + (RB - hf * 28)) * 8 + (KC & 7)) * 8 + r;
}

__device__ __forceinline__ void load_slice_b(uint32_t (&f)[14], uint32_t addr) {
  ldsm4t(f[0], f[1], f[2], f[3], addr);
  ldsm4t(f[4], f[5], f[6], f[7], addr + 512);
  ldsm4t(f[8], f[9], f[10], f[11], addr + 1024);
  ldsm2t(f[12], f[13], addr + 1536);
}
__device__ __forceinline__ void load_slice_a(uint32_t (&f)[4][4], uint32_t addr) {
#pragma unroll
  for (int j = 0; j < 4; j++) ldsm4t(f[j][0], f[j][1], f[j][2], f[j][3], addr + j * 512);
}
__device__ __forceinline__ uint32_t lane_perm16(int lane) {
  return ((((lane >> 3) & 1) * 2 + (lane >> 4)) * 8 + (lane & 7)) * 16;
}
__device__ __forceinline__ void mma4(float (&c)[4], const uint32_t (&a)[4], uint32_t b0, uint32_t b1, bool first) {
  if (first) mma0(c, a[0], a[1], a[2], a[3], b0, b1); else mma(c, a[0], a[1], a[2], a[3], b0, b1);
}

struct StageCursor {
  uint32_t off = 0, idx = 0, par = 0;
  __device__ __forceinline__ void next() { off += STG_BYTES; if (++idx == 3) { idx = 0; off = 0; par ^= 1; } }
};

struct Poll {
  const uint4* p[4];
  uint32_t la, bar;
};
__device__ __forceinline__ void poll_setup(Poll& po, uint32_t sb, int k, int q, int s, int lane, uint32_t nearmask) {
  const uint32_t near = nearmask >> (((s - 1) & 3) * 4);
  const int col = min(32 * k + lane, 111);
  const uint4* src = g_mbox + (q * 8192 + ((s - 1) & 3) * 2048) + col;
#pragma unroll
  for (int j = 0; j < 4; j++) {
    po.p[j] = src + j * 512 + ((near >> j) & 1) * 256;
    asm volatile("" : "+l"(po.p[j]));
  }
  po.la = opaque(sb + R_MEMT + (s & 1) * 7168 + (112 * q + col) * 16);
  po.bar = sb + RB_C1 + (s & 1) * 8;
}
__device__ __forceinline__ void poll_run(const Poll& po, uint32_t sb, int k, int q, uint32_t cstride, int s, int lane, uint32_t ident) {
  if (k == 0) PROF_REC(s, 13);
  if (k == 2) PROF_REC(s, 6);
  float d[4][4];
  int it = 0;
  bool ok;
  do {
    uint4 v[8];
#pragma unroll
    for (int j = 0; j < 4; j++) { v[2 * j] = ld_poll(po.p[j]); v[2 * j + 1] = ld_poll(po.p[j] + 112); }
    uint32_t m = 1;
#pragma unroll
    for (int j = 0; j < 8; j++) {
      if (j < 2) { mma8z(d[2 * (j & 1)], v[j].x, v[j].y, ident); mma8z(d[2 * (j & 1) + 1], v[j].z, v[j].w, ident); }
      else { mma8(d[2 * (j & 1)], v[j].x, v[j].y, ident); mma8(d[2 * (j & 1) + 1], v[j].z, v[j].w, ident); }
      m = min(min(m, min(v[j].x, v[j].y)), min(v[j].z, v[j].w));
    }
    ok = __all_sync(0xffffffffu, m != 0) || ++it > 100000;
  } while (!ok);
  if (k == 0) { PROF_REC(s, 14); PROF_VAL(s, 15, it); }
  if (k == 2) { PROF_REC(s, 7); PROF_VAL(s, 9, it); }
  if (k == 1) PROF_REC(s, 1);
  if (k == 3) PROF_REC(s, 2);
  const uint32_t w0 = pack2(d[0][0] + d[2][0], d[0][1] + d[2][1]), w1 = pack2(d[0][2] + d[2][2], d[0][3] + d[2][3]);
  const uint32_t w2 = pack2(d[1][0] + d[3][0], d[1][1] + d[3][1]), w3 = pack2(d[1][2] + d[3][2], d[1][3] + d[3][3]);
  const bool act = k < 3 || lane < 16;
  if (act) sts128(po.la, w0, w1, w2, w3);
  bar_arrive(BAR_LOC, LOC_COUNT);
#pragma unroll
  for (int i = 1; i < 4; i++) {
    const uint32_t o = (((q + i) & 3) - q) * cstride;
    if (act) st_async_v4(po.la + o, w0, w1, w2, w3, po.bar + o);
  }
}
__device__ __forceinline__ uint32_t ident_frag(int lane) {
  const int r = lane >> 2, p = lane & 3;
  return (2 * p == r ? 0x3F80u : 0u) | (2 * p + 1 == r ? 0x3F800000u : 0u);
}

__device__ __forceinline__ void rec_prefetch(const Params& P, Flags* F, uint32_t sb, int s, uint32_t idx, int g, int hh, int q) {
  const uint32_t st = sb + R_STG + idx * STG_BYTES, mb = sb + RB_STG + 8 * idx;
  mbar_expect(mb, STG_BYTES);
  tma3d(st, &P.tx32, 0, s * 32, 0, mb);
  flag_wait(&F->fkv[s * 8 + g], 8);
  bulk_g2s(st + STG_KA, g_KAF + (size_t)((s * 16 + 2 * g + hh) * 4 + q) * 448, 7168, mb);
  const uint4* vb = g_VBF + (size_t)((s * 16 + 2 * g) * 28 + 7 * q + 3 * hh) * 64;
  bulk_g2s(st + STG_VB, vb, 4096, mb);
  bulk_g2s(st + STG_VB + 4096, vb + 28 * 64, 4096, mb);
}

__host__ __device__ constexpr bool a_in_smem(int t, int k) { return k == 0; }

__device__ __forceinline__ void s2m(float (&e)[4][4], const uint32_t (&f)[4][4], const uint32_t (&tb)[7][2]) {
  mma4(e[0], f[0], tb[0][0], tb[0][1], true);
  mma4(e[1], f[0], tb[1][0], tb[1][1], true);
  mma4(e[2], f[1], tb[2][0], tb[2][1], true);
  mma4(e[3], f[1], tb[3][0], tb[3][1], true);
  mma4(e[0], f[2], tb[4][0], tb[4][1], false);
  mma4(e[1], f[2], tb[5][0], tb[5][1], false);
  mma4(e[2], f[3], tb[6][0], tb[6][1], false);
}

__device__ __forceinline__ void rec_a_warps(Flags* F, uint32_t sb, int g, uint32_t rank, uint32_t cstride, int w, int lane) {
  const int hh = rank >> 2, q = rank & 3;
  uint32_t W[7][7][4];
  if (lane == 0) flag_wait(&F->fw[2 * g + hh], 56);
  __syncwarp();
  const uint32_t l16 = lane * 16;
  const uint32_t aw = sb + R_AW + w * 3584 + l16;
  {
    const uint32_t stg = sb + R_STG + w * 14336 + l16;
#pragma unroll
    for (int rd = 0; rd < 2; rd++) {
#pragma unroll 1
      for (int f = 0; f < (rd ? 21 : 28); f++) {
        const int t = rd * 4 + f / 7, k = f % 7;
        cp16(a_in_smem(t, k) ? aw + t * 512 : stg + f * 512,
             wc_row(2 * g + hh, (7 * w + t) * 2 + ((lane >> 3) & 1), (7 * q + k) * 2 + (lane >> 4), lane & 7));
      }
      cp_commit(); cp_wait<0>(); __syncwarp();
#pragma unroll
      for (int f = 0; f < (rd ? 21 : 28); f++)
        if (!a_in_smem(rd * 4 + f / 7, f % 7)) { uint32_t (&x)[4] = W[rd * 4 + f / 7][f % 7]; ldsm4(x[0], x[1], x[2], x[3], stg + f * 512); }
      __syncwarp();
    }
  }
  fence_async_smem();
  bar_arrive(BAR_W, 288);
  const uint32_t lperm = lane_perm16(lane);
  const uint32_t zero = cstride & 1;
  StageCursor sc;
#pragma unroll 1
  for (int s = 0; s < NSEG; s++) {
    const uint32_t b = s & 1, par = (s >> 1) & 1;
    const uint32_t mt = sb + R_MEMT + b * 7168;
    uint32_t tb[7][2];
    uint32_t x[7][4];
#pragma unroll
    for (int t = 0; t < 7; t++) ldsm4(x[t][0], x[t][1], x[t][2], x[t][3], aw + t * 512);
    uint4 kf[3];
    mbar_wait(sb + RB_STG + 8 * sc.idx, sc.par);
#pragma unroll
    for (int k = 0; k < 3; k++) kf[k] = lds128(sb + R_STG + sc.off + STG_KA + w * 1792 + k * 512 + l16);
    const uint2 kl = lds64(sb + R_STG + sc.off + STG_KA + w * 1792 + 1536 + (l16 >> 1));
    if (w == 0) PROF_REC(s, 0);
    bar_sync(BAR_LOC, LOC_COUNT);
    {
      float c[7][4];
      uint32_t f[14], fa[4][4];
      load_slice_b(f, mt + q * 1792 + l16);
      {
        float e0[4], e1[4];
        mma0(e0, f[0], f[1], f[2], f[3], kf[0].x, kf[0].y);
        mma0(e1, f[0], f[1], f[2], f[3], kf[0].z, kf[0].w);
        mma(e0, f[4], f[5], f[6], f[7], kf[1].x, kf[1].y);
        mma(e1, f[4], f[5], f[6], f[7], kf[1].z, kf[1].w);
        mma(e0, f[8], f[9], f[10], f[11], kf[2].x, kf[2].y);
        mma(e1, f[8], f[9], f[10], f[11], kf[2].z, kf[2].w);
        mma8(e0, f[12], f[13], kl.x);
        mma8(e1, f[12], f[13], kl.y);
#pragma unroll
        for (int k = 0; k < 7; k++)
#pragma unroll
          for (int t = 0; t < 3; t++) {
            if (k == 0) mma4(c[t], x[t], f[0], f[1], true); else mma4(c[t], W[t][k], f[2 * k], f[2 * k + 1], false);
          }
        const uint32_t word = pack2(e0[0] + e1[2], e0[1] + e1[3]);
        sts32(sb + R_SX + b * 4096 + rank * 512 + w * 128 + (l16 >> 2), word);
        bar_arrive(BAR_FW, 160);
      }
      uint32_t dep = 0;
      ldsm2t(f[4], f[5], mt + q * 1792 + 512 + l16);
#pragma unroll
      for (int t = 0; t < 3; t++) { tb[t][0] = movm(pack2(c[t][0], c[t][1])); tb[t][1] = movm(pack2(c[t][2], c[t][3])); }
#pragma unroll
      for (int k = 0; k < 7; k++) {
        if (k == 6) dep = __float_as_uint(c[3][0]) & zero;
#pragma unroll
        for (int t = 3; t < 7; t++) {
          if (k == 0) mma4(c[t], x[t], f[0], f[1], true); else mma4(c[t], W[t][k], f[2 * k], f[2 * k + 1], false);
        }
      }
      bar_arrive(BAR_AB + w + dep, 64);
      const bool early = mbar_test(sb + RB_C1 + 8 * b + dep, par);
      load_slice_a(fa, mt + w * 1792 + lperm);
#pragma unroll
      for (int t = 3; t < 7; t++) { tb[t][0] = movm(pack2(c[t][0], c[t][1])); tb[t][1] = movm(pack2(c[t][2], c[t][3])); }
      const uint32_t l8 = opaque(l16) >> 1;
      const uint32_t dst = sb + R_SM + b * 2048 + rank * 256 + l8, bar = sb + RB_SM + 8 * b;
      const uint32_t o0 = (2 * w - rank) * cstride, o1 = o0 + cstride;
      const uint32_t d0 = dst + o0, d1 = dst + o1, b0 = bar + o0, b1 = bar + o1;
      float e[4][4];
      if (!early) {
        mbar_wait(sb + RB_C1 + 8 * b, par);
        load_slice_a(fa, mt + w * 1792 + lperm);
      }
      if (w == 0) PROF_REC(s, 3);
      s2m(e, fa, tb);
      sts64f(sb + R_AR1 + w * 256 + l8, (e[0][0] + e[2][0]) + (e[1][2] + e[3][2]), (e[0][1] + e[2][1]) + (e[1][3] + e[3][3]));
      bar_sync(BAR_A, 128);
      const float2 p0 = lds64f(sb + R_AR1 + l8), p1 = lds64f(sb + R_AR1 + 256 + l8),
                   p2 = lds64f(sb + R_AR1 + 512 + l8), p3 = lds64f(sb + R_AR1 + 768 + l8);
      const float v0 = (p0.x + p1.x) + (p2.x + p3.x), v1 = (p0.y + p1.y) + (p2.y + p3.y);
      st_async_v2f(d0, v0, v1, b0);
      st_async_v2f(d1, v0, v1, b1);
    }
    if (w == 0) PROF_REC(s, 4);
    {
      mbar_wait(sb + RB_SM + 8 * b, par);
      delay(EXP_DELAY);
      const uint32_t ln = opaque(l16) >> 4;
      const uint32_t xs_lane = (ln & 15) * 128, xs_x = ((ln >> 4) ^ (ln & 7)) << 4;
      float e[2][4];
      constexpr int NEXP = 7;
#pragma unroll
      for (int t = 0; t < NEXP; t++) {
        const int kc = 14 * w + 2 * t;
        const uint32_t ka = sb + R_STG + sc.off + (kc >> 3) * 4096 + xs_lane + (((kc & 7) << 4) ^ xs_x);
#pragma unroll
        for (int m = 0; m < 2; m++) {
          uint32_t a[4];
          ldsm4(a[0], a[1], a[2], a[3], ka + m * 2048);
          mma4(e[m], a, tb[t][0], tb[t][1], t == 0);
        }
      }
      sts128f(sb + R_AR2 + w * 1024 + l16, e[0][0], e[0][1], e[0][2], e[0][3]);
      sts128f(sb + R_AR2 + w * 1024 + 512 + l16, e[1][0], e[1][1], e[1][2], e[1][3]);
      bar_sync(BAR_A, 128);
      const uint32_t ra = sb + R_AR2 + w * 256 + (l16 >> 1);
      const float2 p0 = lds64f(ra), p1 = lds64f(ra + 1024), p2 = lds64f(ra + 2048), p3 = lds64f(ra + 3072);
      reinterpret_cast<float2*>(g_SXM)[((s * 16 + 2 * g + hh) * 4 + q) * 128 + w * 32 + ln] =
          make_float2((p0.x + p1.x) + (p2.x + p3.x), (p0.y + p1.y) + (p2.y + p3.y));
      __syncwarp();
      if (lane == 0) mbar_arrive(sb + RB_EXP + 8 * b);
      if (w == 0) PROF_REC(s, 5);
      sc.next();
    }
  }
}

template <bool TWO>
__device__ __forceinline__ void rec_b_warps(Flags* F, uint32_t sb, int g, uint32_t rank, uint32_t cstride, int w, int lane) {
  const int hh = rank >> 2, q = rank & 3;
  uint32_t X[28][4];
  if (lane < 2) flag_wait(&F->fw[16 + 2 * g + lane], 56);
  __syncwarp();
  const int tile = TWO ? 7 * q + 4 * hh + w : 7 * q + 3;
  const uint32_t l16 = lane * 16;
  const uint32_t bw = sb + R_BW + w * 14336 + l16;
  {
    const uint32_t stg = sb + R_STG + 57344 + w * 14336 + l16;
#pragma unroll 1
    for (int f = 0; f < (TWO ? 56 : 28); f++) {
      const int j = f / 7, k = f % 7, i0 = (lane >> 3) & 1;
      const int mat = 16 + 2 * g + (TWO ? (j >= 4) : i0), RB = tile * 2 + (TWO ? i0 : hh);
      cp16(f < 28 ? stg + f * 512 : bw + (f - 28) * 512, wc_row(mat, RB, (7 * ((q + j) & 3) + k) * 2 + (lane >> 4), lane & 7));
    }
    cp_commit(); cp_wait<0>(); __syncwarp();
#pragma unroll
    for (int f = 0; f < 28; f++) ldsm4(X[f][0], X[f][1], X[f][2], X[f][3], stg + f * 512);
  }
  fence_async_smem();
  bar_arrive(BAR_W, 288);
#pragma unroll 1
  for (int s = 0; s < NSEG; s++) {
    const uint32_t b = s & 1;
    const uint32_t mt = sb + R_MEMT + b * 7168 + l16;
    if (w == 0) PROF_REC(s, 8);
    constexpr int NY = B_RING;
    uint32_t y[NY][4];
    uint32_t f[4][14];
    if (TWO) {
      bar_sync(BAR_LOC, LOC_COUNT);
      if (w == 0) PROF_REC(s, 11);
      delay(LAND_DELAY);
#pragma unroll
      for (int i = 0; i < NY; i++) ldsm4(y[i][0], y[i][1], y[i][2], y[i][3], bw + i * 512);
      ldsm4t(f[0][4], f[0][5], f[0][6], f[0][7], mt + q * 1792 + 512);
      ldsm4t(f[0][8], f[0][9], f[0][10], f[0][11], mt + q * 1792 + 1024);
      ldsm2t(f[0][12], f[0][13], mt + q * 1792 + 1536);
      bar_sync(BAR_AB + w, 64);
      ldsm4t(f[0][0], f[0][1], f[0][2], f[0][3], mt + q * 1792);
    } else {
      if (s > 0) {
        Poll po;
        poll_setup(po, sb, 3, q, s, lane, lds32(sb + R_NEAR));
        mbar_wait(sb + RB_SM + 8 * (b ^ 1), ((s - 1) >> 1) & 1);
        delay(POLL_DELAY_B);
        poll_run(po, sb, 3, q, cstride, s, lane, ident_frag(lane));
      } else bar_arrive(BAR_LOC, LOC_COUNT);
      bar_sync(BAR_AB + w, 64);
      load_slice_b(f[0], mt + q * 1792);
    }
    float c[4][4];
#pragma unroll
    for (int j = 0; j < 28; j++) {
      const int pos = j / 7, k = j % 7;
      if (j == 7) {
        mbar_wait(sb + RB_C1 + 8 * b, (s >> 1) & 1);
        delay(U_DELAY);
        load_slice_b(f[1], mt + ((q + 1) & 3) * 1792);
        if (TWO) {
#pragma unroll
          for (int i = 0; i < 7; i++) ldsm4(y[i][0], y[i][1], y[i][2], y[i][3], bw + (i + NY) * 512);
        }
      }
      if (k == 1 && pos >= 1 && pos < 3) load_slice_b(f[pos + 1], mt + ((q + pos + 1) & 3) * 1792);
      mma4(c[j & 1], X[j], f[pos][2 * k], f[pos][2 * k + 1], j < 2);
      if (TWO) {
        mma4(c[2 + (j & 1)], y[j % NY], f[pos][2 * k], f[pos][2 * k + 1], j < 2);
        if (j >= 7 && j + NY < 28) ldsm4(y[j % NY][0], y[j % NY][1], y[j % NY][2], y[j % NY][3], bw + (j + NY) * 512);
      }
    }
    {
      const uint32_t x0 = pack2(c[0][0] + c[1][0], c[0][1] + c[1][1]), x1 = pack2(c[0][2] + c[1][2], c[0][3] + c[1][3]);
      uint4* ud = g_UF + ((s * 8 + g) * 28 + tile) * 32 + lane;
      if (TWO) {
        const uint32_t y0 = pack2(c[2][0] + c[3][0], c[2][1] + c[3][1]), y1 = pack2(c[2][2] + c[3][2], c[2][3] + c[3][3]);
        sts128(sb + R_UFR + w * 512 + l16, x0, x1, y0, y1);
        __syncwarp();
        if (lane == 0) mbar_arrive(sb + RB_SM + 8 * b);
        *ud = make_uint4(x0, x1, y0, y1);
      } else {
        sts128(sb + R_UFR + w * 512 + l16, hh ? 0u : x0, hh ? x0 : 0u, hh ? 0u : x1, hh ? x1 : 0u);
        __syncwarp();
        if (lane == 0) mbar_arrive(sb + RB_SM + 8 * b);
        reinterpret_cast<uint32_t*>(ud)[hh] = x0;
        reinterpret_cast<uint32_t*>(ud)[2 + hh] = x1;
      }
      if (w == 0) PROF_REC(s, 12);
      __syncwarp();
      if (lane == 0) mbar_arrive(sb + RB_EXP + 8 * b);
    }
  }
}

__device__ __forceinline__ void sum_sx(float (&sx)[4][4], uint32_t addr, uint32_t ident) {
#pragma unroll
  for (int t = 0; t < 4; t++) {
    uint32_t a0, a1, a2, a3;
    ldsm4(a0, a1, a2, a3, addr + t * 128);
    mma0(sx[t], a0, a1, a2, a3, ident, ident);
  }
#pragma unroll
  for (int t = 0; t < 4; t++) {
    uint32_t a0, a1, a2, a3;
    ldsm4(a0, a1, a2, a3, addr + 1024 + t * 128);
    mma(sx[t], a0, a1, a2, a3, ident, ident);
  }
}
__device__ __forceinline__ void load_vb(uint4 (&v)[2][4], int hd, uint32_t vb0, uint32_t vb1) {
#pragma unroll
  for (int t = 0; t < 2; t++) {
    const uint32_t vb = (t ? vb1 : vb0) + hd * 4096;
    v[t][2 * hd] = lds128(vb); v[t][2 * hd + 1] = lds128(vb + 512);
  }
}
__device__ __forceinline__ void token_pv(float (&ax)[2][2][4], float (&lx0)[4], float (&lx1)[4], const float (&sx)[4][4],
                                         float m0, float m1, const uint4 (&v)[2][4]) {
  const uint32_t ones = 0x3F803F80u;
  uint32_t e0[4], e1[4];
#pragma unroll
  for (int t = 0; t < 4; t++) e0[t] = pack2(ex2(sx[t][0] - m0), ex2(sx[t][1] - m0));
#pragma unroll
  for (int t = 0; t < 4; t++) e1[t] = pack2(ex2(sx[t][2] - m1), ex2(sx[t][3] - m1));
  mma0(lx0, ones, ones, ones, ones, e0[0], e0[1]);
  mma(lx0, ones, ones, ones, ones, e0[2], e0[3]);
  mma0(lx1, ones, ones, ones, ones, e1[0], e1[1]);
  mma(lx1, ones, ones, ones, ones, e1[2], e1[3]);
#pragma unroll
  for (int t = 0; t < 2; t++) {
    mma0(ax[t][0], v[t][0].x, v[t][0].y, v[t][0].z, v[t][0].w, e0[0], e0[1]);
    mma(ax[t][0], v[t][1].x, v[t][1].y, v[t][1].z, v[t][1].w, e0[2], e0[3]);
    mma0(ax[t][1], v[t][2].x, v[t][2].y, v[t][2].z, v[t][2].w, e1[0], e1[1]);
    mma(ax[t][1], v[t][3].x, v[t][3].y, v[t][3].z, v[t][3].w, e1[2], e1[3]);
  }
}
__device__ __forceinline__ void mem_pv(uint32_t (&wd)[4], float (&ax)[2][2][4], float (&lx0)[4], float (&lx1)[4],
                                       float s00, float s01, float s10, float s11, const uint4& u0, const uint4& u1) {
  const uint32_t ones = 0x3F803F80u;
  const uint32_t em0 = pack2(ex2(s00), ex2(s01)), em1 = pack2(ex2(s10), ex2(s11));
  mma8(lx0, ones, ones, em0);
  mma8(lx1, ones, ones, em1);
  mma8(ax[0][0], u0.x, u0.y, em0);
  mma8(ax[0][1], u0.z, u0.w, em1);
  mma8(ax[1][0], u1.x, u1.y, em0);
  mma8(ax[1][1], u1.z, u1.w, em1);
  const float i00 = rcp(lx0[0]), i01 = rcp(lx0[1]), i10 = rcp(lx1[0]), i11 = rcp(lx1[1]);
#pragma unroll
  for (int t = 0; t < 2; t++) {
    const uint32_t w0 = pack2(fmaf(ax[t][0][0], i00, ax[t][1][0] * i10), fmaf(ax[t][0][1], i01, ax[t][1][1] * i11));
    const uint32_t w1 = pack2(fmaf(ax[t][0][2], i00, ax[t][1][2] * i10), fmaf(ax[t][0][3], i01, ax[t][1][3] * i11));
    wd[2 * t] = w0 ? w0 : 0x8000u; wd[2 * t + 1] = w1 ? w1 : 0x8000u;
  }
}

__device__ __forceinline__ void rec_c_warps(const Params& P, Flags* F, uint32_t sb, int g, uint32_t rank, uint32_t cstride, int wc, int lane) {
  const int hh = rank >> 2, q = rank & 3;
  if (wc == 0) {
    bar_sync(BAR_W, 288);
    if (lane == 0) {
      rec_prefetch(P, F, sb, 0, 0, g, hh, q);
      rec_prefetch(P, F, sb, 1, 1, g, hh, q);
      uint32_t idx = 2;
#pragma unroll 1
      for (int s = 0; s < NSEG; s++) {
        mbar_wait(sb + RB_SX + 8 * (s & 1), (s >> 1) & 1);
        if (s + 2 < NSEG) rec_prefetch(P, F, sb, s + 2, idx, g, hh, q);
        idx = idx == 2 ? 0 : idx + 1;
        mbar_wait(sb + RB_EXP + 8 * (s & 1), (s >> 1) & 1);
        fence_gpu();
        red_add(&F->fseg[s], 1);
      }
    }
    return;
  }
  if (wc == 1) {
#pragma unroll 1
    for (int s = 0; s < NSEG; s++) {
      Poll po;
      poll_setup(po, sb, 2, q, s, lane, lds32(sb + R_NEAR));
      if (s > 0) mbar_wait(sb + RB_SM + 8 * ((s - 1) & 1), ((s - 1) >> 1) & 1);
      if (lane == 0) {
        mbar_expect(sb + RB_C1 + 8 * (s & 1), s > 0 ? 5376 : 0);
        mbar_expect(sb + RB_SM + 8 * (s & 1), 2048);
      }
      __syncwarp();
      if (s > 0) { delay(POLL_DELAY_B); poll_run(po, sb, 2, q, cstride, s, lane, ident_frag(lane)); }
      else bar_arrive(BAR_LOC, LOC_COUNT);
      const uint32_t src = sb + R_SX + (s & 1) * 4096 + rank * 512 + lane * 16, bar = sb + RB_SX + 8 * (s & 1);
      bar_sync(BAR_FW, 160);
      const uint4 v = lds128(src);
      if (lane == 0) mbar_expect(bar, 3584);
#pragma unroll
      for (int i = 1; i < 8; i++) {
        const uint32_t o = (((rank + i) & 7) - rank) * cstride;
        st_async_v4(src + o, v.x, v.y, v.z, v.w, bar + o);
      }
    }
    mbar_wait(sb + RB_SX + 8, 1);
    mbar_wait(sb + RB_SM + 8, 1);
    return;
  }
  const int w = wc - 2;
  const int tl0 = 4 * hh + 2 * w, tl1 = w ? 3 : 4 * hh + 1;
  uint32_t* mb0 = reinterpret_cast<uint32_t*>(g_mbox + q * 8192 + (g >> 1) * 512 + (g & 1) * 112) + lane + tl0 * 64;
  const int dt = (tl1 - tl0) * 64;
  const bool st_lo = w == 0 || hh == 0, st_hi = w == 0 || hh == 1;
#pragma unroll 1
  for (int sl = 0; sl < 8; sl++) {
    uint32_t* o = mb0 + (sl >> 1) * 8192 + (sl & 1) * 1024;
    st_relaxed(o, 0); st_relaxed(o + 32, 0);
    if (st_lo) st_relaxed(o + dt, 0);
    if (st_hi) st_relaxed(o + dt + 32, 0);
  }
  __syncwarp();
  if (lane == 0) {
    fence_gpu(); red_add(&F->frec, 1);
    uint32_t mask = 0;
#pragma unroll 1
    for (int i = 0; i < 8; i++) {
      unsigned* pr = reinterpret_cast<unsigned*>(g_mbox + q * 8192 + (w * 8 + i) * 512 + 240);
      uint32_t best[2] = {~0u, ~0u};
#pragma unroll 1
      for (int rep = 0; rep < PROBE_REPS; rep++) {
        uint32_t t0, t1, o;
        asm volatile("mov.u32 %0, %%clock;" : "=r"(t0) :: "memory");
        asm volatile("atom.relaxed.gpu.global.exch.b32 %0, [%1], %2;" : "=r"(o) : "l"(pr + (rep & 1) * 1024), "r"(rep) : "memory");
        asm volatile("{.reg .u32 t; and.b32 t, %1, 0; mov.u32 %0, %%clock; add.u32 %0, %0, t;}" : "=r"(t1) : "r"(o) : "memory");
        if (o == 0xdeadbeefu) g_err = 9;
        asm volatile("mov.u32 %0, %%clock;" : "=r"(t1) :: "memory");
        if (rep & 1) best[1] = min(best[1], t1 - t0); else best[0] = min(best[0], t1 - t0);
      }
      mask |= (best[1] < best[0] ? 1u : 0u) << (w * 8 + i);
    }
    asm volatile("red.shared.or.b32 [%0], %1;" ::"r"(sb + R_NEAR), "r"(mask) : "memory");
    flag_wait(&F->frec, 128);
  }
  __syncwarp();
  const uint32_t ident = ident_frag(lane);
  const uint32_t sx_l = (((lane >> 3) & 1) * 4 + (lane >> 4)) * 512 + (lane & 7) * 16;
  const uint32_t l16 = lane * 16;
  StageCursor sc;
  uint32_t nearmask = 0;
#pragma unroll 1
  for (int s = 0; s < NSEG; s++) {
    const uint32_t b = s & 1, par = (s >> 1) & 1;
    if (s > 0) {
      const uint32_t t0 = now();
      Poll po;
      poll_setup(po, sb, w, q, s, opaque(lane), nearmask);
      delay_from(t0, POLL_DELAY_C);
      poll_run(po, sb, w, q, cstride, s, lane, ident);
    }
    else bar_arrive(BAR_LOC, LOC_COUNT);
    if (w == 0) PROF_REC(s, 16);
    if (s == NSEG - 1) break;
    const uint32_t vb0 = sb + R_STG + sc.off + STG_VB + (tl0 - 3 * hh) * 1024 + l16, vb1 = vb0 + (tl1 - tl0) * 1024;
    uint32_t* o0 = mb0 + (s & 3) * 8192;
    uint32_t* o1 = o0 + dt;
    asm volatile("" : "+l"(o0), "+l"(o1));
    const uint32_t sa = opaque(sb + R_SM + b * 2048 + (l16 >> 1));
    mbar_wait(sb + RB_STG + 8 * sc.idx, sc.par);
    uint4 v[2][4];
    if (s >= 3) {
      uint32_t* o = mb0 + ((s - 3) & 3) * 8192;
#pragma unroll
      for (int cp = 0; cp < 2; cp++) {
        st_relaxed(o + cp * 1024, 0); st_relaxed(o + cp * 1024 + 32, 0);
        if (st_lo) st_relaxed(o + cp * 1024 + dt, 0);
        if (st_hi) st_relaxed(o + cp * 1024 + dt + 32, 0);
      }
    }
    delay(100);
    load_vb(v, 0, vb0, vb1);
    mbar_wait(sb + RB_SX + 8 * b, par);
    if (w == 0) PROF_REC(s, 17);
    float ax[2][2][4], lx0[4], lx1[4], rng;
    {
      float sx[4][4];
      sum_sx(sx, sb + R_SX + b * 4096 + sx_l, ident);
      load_vb(v, 1, vb0, vb1);
      token_pv(ax, lx0, lx1, sx, 0.f, 0.f, v);
      rng = 0.f;
#pragma unroll
      for (int t = 0; t < 4; t++) rng = fmaxf(fmaxf(rng, fmaxf(fabsf(sx[t][0]), fabsf(sx[t][1]))), fmaxf(fabsf(sx[t][2]), fabsf(sx[t][3])));
    }
    nearmask = __shfl_sync(0xffffffffu, lds32(sb + R_NEAR), 0);
    if (w == 0) PROF_REC(s, 18);
    mbar_wait(sb + RB_SM + 8 * b, par);
    if (w == 0) PROF_REC(s, 20);
    const float2 p0 = lds64f(sa), p1 = lds64f(sa + 256), p2 = lds64f(sa + 512), p3 = lds64f(sa + 768);
    const float2 q0 = lds64f(sa + 1024), q1 = lds64f(sa + 1280), q2 = lds64f(sa + 1536), q3 = lds64f(sa + 1792);
    const uint4 u0 = lds128(sb + R_UFR + w * 1024 + l16), u1 = lds128(sb + R_UFR + w * 1024 + 512 + l16);
    const float s00 = (p0.x + p1.x) + (p2.x + p3.x), s01 = (p0.y + p1.y) + (p2.y + p3.y);
    const float s10 = (q0.x + q1.x) + (q2.x + q3.x), s11 = (q0.y + q1.y) + (q2.y + q3.y);
    uint32_t wd[4];
    mem_pv(wd, ax, lx0, lx1, s00, s01, s10, s11, u0, u1);
    rng = fmaxf(fmaxf(rng, fmaxf(fabsf(s00), fabsf(s01))), fmaxf(fabsf(s10), fabsf(s11)));
    const bool safe = __all_sync(0xffffffffu, rng <= SAFE_RANGE);
#pragma unroll
    for (int cp = 0; cp < 2; cp++) {
      if (safe) st_relaxed(o0 + cp * 1024, wd[0]);
      if (safe) st_relaxed(o0 + cp * 1024 + 32, wd[1]);
      if (safe && st_lo) st_relaxed(o1 + cp * 1024, wd[2]);
      if (safe && st_hi) st_relaxed(o1 + cp * 1024 + 32, wd[3]);
    }
    if (w == 0) { PROF_REC(s, 22); if (s == 10) PROF_VAL(s, 19, lds32(sb + R_NEAR)); }
    if (!safe) {
      float sx[4][4];
      sum_sx(sx, sb + R_SX + b * 4096 + sx_l, ident);
      float m0 = fmaxf(s00, s01), m1 = fmaxf(s10, s11);
#pragma unroll
      for (int t = 0; t < 4; t++) { m0 = fmaxf(m0, fmaxf(sx[t][0], sx[t][1])); m1 = fmaxf(m1, fmaxf(sx[t][2], sx[t][3])); }
      m0 = fmaxf(m0, __shfl_xor_sync(0xffffffffu, m0, 1)); m1 = fmaxf(m1, __shfl_xor_sync(0xffffffffu, m1, 1));
      m0 = fmaxf(m0, __shfl_xor_sync(0xffffffffu, m0, 2)); m1 = fmaxf(m1, __shfl_xor_sync(0xffffffffu, m1, 2));
      load_vb(v, 0, vb0, vb1);
      load_vb(v, 1, vb0, vb1);
      token_pv(ax, lx0, lx1, sx, m0, m1, v);
      const uint4 t0 = lds128(sb + R_UFR + w * 1024 + l16), t1 = lds128(sb + R_UFR + w * 1024 + 512 + l16);
      mem_pv(wd, ax, lx0, lx1, s00 - m0, s01 - m0, s10 - m1, s11 - m1, t0, t1);
#pragma unroll
      for (int cp = 0; cp < 2; cp++) {
        st_relaxed(o0 + cp * 1024, wd[0]); st_relaxed(o0 + cp * 1024 + 32, wd[1]);
        if (st_lo) st_relaxed(o1 + cp * 1024, wd[2]);
        if (st_hi) st_relaxed(o1 + cp * 1024 + 32, wd[3]);
      }
    }
    if (w == 0) PROF_REC(s, 21);
    sc.next();
  }
}

__device__ __forceinline__ void rec_init(const Params& P, uint32_t sb, char* smem) {
  const int tid = threadIdx.x;
  if (tid == 0) {
    for (int i = 0; i < 2; i++) { mbar_init(sb + RB_C1 + 8 * i, 1); mbar_init(sb + RB_SX + 8 * i, 1); mbar_init(sb + RB_SM + 8 * i, 5); mbar_init(sb + RB_EXP + 8 * i, 8); }
    for (int i = 0; i < 3; i++) mbar_init(sb + RB_STG + 8 * i, 1);
    sts32(sb + R_NEAR, 0);
    asm volatile("fence.mbarrier_init.release.cluster;" ::: "memory");
  }
  bf16* mt = reinterpret_cast<bf16*>(smem + R_MEMT);
  for (int i = tid; i < 8 * DM; i += NTHREADS) mt[(i % DM) * 8 + i / DM] = P.mem0[i];
}

__device__ __forceinline__ int own_lane() { const int l = read_tid() & 31; return __shfl_sync(0xffffffffu, l, l); }

template <bool HELPER>
__global__ void __launch_bounds__(NTHREADS, 1) fused_kernel(const __grid_constant__ Params P, int nmain) {
  extern __shared__ __align__(1024) char smem[];
  const uint32_t sb = __shfl_sync(0xffffffffu, smem_u32(smem), 0);
  const int tid = threadIdx.x, wg = tid >> 7;
  const int cta = HELPER ? nmain + blockIdx.x : blockIdx.x;
  uint32_t crank; asm volatile("mov.u32 %0, %%cluster_ctarank;" : "=r"(crank));
  if (!HELPER) asm volatile("griddepcontrol.launch_dependents;");
  if (tid == 0) { PROF_CTA(cta, 0); PROF_CLK(cta, 4); }
  const unsigned epoch = __ldcg(&g_epoch[cta]);
  Flags* F = &g_flags[epoch & 1];
  const bool is_rec = !HELPER && blockIdx.x < 64;
  if (tid == 0) gemm_init_barriers(sb);
  if (cta == nmain - 1) {
    unsigned* o = reinterpret_cast<unsigned*>(&g_flags[(epoch & 1) ^ 1]);
    for (int i = tid; i < FLAG_WORDS; i += NTHREADS) o[i] = 0;
  }
  __syncthreads();
  {
    volatile unsigned* slot = reinterpret_cast<volatile unsigned*>(smem + G_MISC);
    int item = HELPER ? -1 : cta;
#pragma unroll 1
    for (uint32_t par = 0;; par ^= 1) {
      if (item < 0) {
        if (tid == 0) *slot = nmain + atomicAdd(&F->q_w, 1);
        __syncthreads();
        item = *slot;
        __syncthreads();
        if (item >= 128) break;
      }
      phase_w(P, F, item, sb, par);
      item = -1;
    }
  }
  if (tid == 0) PROF_CTA(cta, 1);
  if (tid == 0) g_epoch[cta] = epoch + 1;
  if (is_rec) rec_init(P, sb, smem);
  __syncthreads();
  cluster_sync();
  if (is_rec) {
    const int g = blockIdx.x >> 3;
    const uint32_t cstride = __shfl_sync(0xffffffffu, mapa(sb, 1) - mapa(sb, 0), 0);
    const uint32_t rank = __shfl_sync(0xffffffffu, crank, 0);
    const int w = __shfl_sync(0xffffffffu, (tid >> 5) & 3, 0);
    if (wg == 0) { reg_inc<240>(); rec_a_warps(F, sb, g, rank, cstride, w, own_lane()); }
    else if (wg == 1) { reg_inc<184>(); if (w < 3) rec_b_warps<true>(F, sb, g, rank, cstride, w, own_lane()); else rec_b_warps<false>(F, sb, g, rank, cstride, w, own_lane()); }
    else { reg_dec<80>(); rec_c_warps(P, F, sb, g, rank, cstride, w, own_lane()); }
  } else {
    if (wg == 2) {
      reg_dec<40>();
      const int t2 = read_tid();
      if (t2 == 256) gemm_producer(P, F, sb, crank);
      else if ((t2 >> 5) == 9) gemm_publisher(F, sb, crank, t2 & 31);
      else if (!HELPER && t2 >= 320)
        for (int i = (cta - 64) * 2 + (t2 >> 5) - 10; i < 128; i += (nmain - 64) * 2) gate_rows(P, F, i, t2 & 31);
    } else {
      reg_inc<232>();
      gemm_consumer(F, sb, crank, cta);
      if (threadIdx.x == 0) PROF_CTA(cta, 2);
      tail_worker(P, F, sb, smem, cta);
    }
  }
  if (threadIdx.x == 0) { PROF_CTA(cta, 3); PROF_CLK(cta, 5); }
  __syncwarp();
  cluster_sync();
}

extern "C" void kernel_launch(void* const* d_in, const int* in_sizes, int n_in, void* d_out, int out_size) {
  (void)in_sizes; (void)n_in; (void)out_size;
  typedef CUresult (*EncodeFn)(CUtensorMap*, CUtensorMapDataType, cuuint32_t, void*, const cuuint64_t*, const cuuint64_t*,
                               const cuuint32_t*, const cuuint32_t*, CUtensorMapInterleave, CUtensorMapSwizzle,
                               CUtensorMapL2promotion, CUtensorMapFloatOOBfill);
  static EncodeFn enc = nullptr;
  if (!enc) {
    void* fn = nullptr; cudaDriverEntryPointQueryResult qr;
    cudaGetDriverEntryPoint("cuTensorMapEncodeTiled", &fn, cudaEnableDefault, &qr);
    enc = (EncodeFn)fn;
  }
  Params P;
  auto map2d = [&](CUtensorMap* m, void* base, uint64_t cols, uint64_t rows, uint32_t boxrows) {
    cuuint64_t dim[2] = {cols, rows}, str[1] = {cols * 2};
    cuuint32_t box[2] = {64, boxrows}, es[2] = {1, 1};
    enc(m, CU_TENSOR_MAP_DATA_TYPE_BFLOAT16, 2, base, dim, str, box, es, CU_TENSOR_MAP_INTERLEAVE_NONE,
        CU_TENSOR_MAP_SWIZZLE_128B, CU_TENSOR_MAP_L2_PROMOTION_L2_256B, CU_TENSOR_MAP_FLOAT_OOB_FILL_NONE);
  };
  map2d(&P.tq, d_in[2], NH * DH, DM, 64);
  map2d(&P.tk, d_in[3], NH * DH, DM, 224);
  map2d(&P.tv, d_in[4], NH * DH, DM, 224);
  map2d(&P.to, d_in[5], DM, NH * DH, 64);
  map2d(&P.tx128, d_in[0], DM, SEQ, 128);
  {
    cuuint64_t dim[3] = {64, SEQ, 7}, str[2] = {DM * 2, 128};
    cuuint32_t box[3] = {64, 32, 7}, es[3] = {1, 1, 1};
    enc(&P.tx32, CU_TENSOR_MAP_DATA_TYPE_BFLOAT16, 3, d_in[0], dim, str, box, es, CU_TENSOR_MAP_INTERLEAVE_NONE,
        CU_TENSOR_MAP_SWIZZLE_128B, CU_TENSOR_MAP_L2_PROMOTION_L2_128B, CU_TENSOR_MAP_FLOAT_OOB_FILL_NONE);
  }
  P.x = (const bf16*)d_in[0]; P.mem0 = (const bf16*)d_in[1];
  P.wr = (const bf16*)d_in[8]; P.wgate = (const bf16*)d_in[9]; P.wup = (const bf16*)d_in[10]; P.wdown = (const bf16*)d_in[11];
  P.gatew = (const bf16*)d_in[12];
  P.out = (bf16*)d_out;

  static int ncl = 0, nhelp = 0;
  cudaLaunchConfig_t cfg = {};
  cudaLaunchAttribute at[2];
  cfg.blockDim = dim3(NTHREADS); cfg.dynamicSmemBytes = SMEM_BYTES; cfg.stream = cudaStreamPerThread;
  at[0].id = cudaLaunchAttributeClusterDimension; at[0].val.clusterDim.x = 8; at[0].val.clusterDim.y = 1; at[0].val.clusterDim.z = 1;
  cfg.attrs = at; cfg.numAttrs = 1;
  if (ncl == 0) {
    cudaFuncSetAttribute(fused_kernel<false>, cudaFuncAttributeMaxDynamicSharedMemorySize, SMEM_BYTES);
    cudaFuncSetAttribute(fused_kernel<true>, cudaFuncAttributeMaxDynamicSharedMemorySize, SMEM_BYTES);
    cfg.gridDim = dim3(128);
    int n = 0, dev = 0, sms = 0;
    cudaOccupancyMaxActiveClusters(&n, fused_kernel<false>, &cfg);
    cudaGetDevice(&dev);
    cudaDeviceGetAttribute(&sms, cudaDevAttrMultiProcessorCount, dev);
    if (n > 16) n = 16;
    if (n < 9) n = 9;
    ncl = n;
    nhelp = (sms - n * 8) & ~1;
    if (nhelp < 0) nhelp = 0;
    if (nhelp > 64) nhelp = 64;
  }
  const int nmain = ncl * 8;
  cfg.gridDim = dim3(nmain);
  cudaLaunchKernelEx(&cfg, fused_kernel<false>, P, nmain);
  if (nhelp > 0) {
    cfg.gridDim = dim3(nhelp);
    at[0].val.clusterDim.x = 2;
    at[1].id = cudaLaunchAttributeProgrammaticStreamSerialization; at[1].val.programmaticStreamSerializationAllowed = 1;
    cfg.numAttrs = 2;
    cudaLaunchKernelEx(&cfg, fused_kernel<true>, P, nmain);
  }
}
```
